```python
import torch

def _softmax(x, axis=-1):
    return torch.softmax(x, dim=axis)
def _gelu(x):
    return torch.nn.functional.gelu(x, approximate="tanh")
def _silu(x):
    return torch.nn.functional.silu(x)
def _sigmoid(x):
    return torch.sigmoid(x)
def _layernorm(x, axis=-1, eps=1e-5):
    m = x.mean(dim=axis, keepdim=True)
    v = x.var(dim=axis, keepdim=True, unbiased=False)
    return (x - m) / torch.sqrt(v + eps)
def _scatter_add(tgt, idx, src, axis=0):
    return tgt.clone().index_add_(axis, idx, src)
def _segment_sum(src, seg, n):
    out = torch.zeros((n,) + src.shape[1:], dtype=src.dtype)
    return out.index_add_(0, seg, src)
def _pad(x, pw):
    flat = tuple(v for pair in reversed(pw) for v in pair)
    return torch.nn.functional.pad(x, flat)

kernel_name = 'standalone__low_rank_proj_linformer__decode'

def setup_inputs():

    _w = (lambda a: (lambda t: t.to(torch.bfloat16) if t.is_floating_point() else t)(torch.as_tensor(a)))
    B, H, Sq, Skv, Dh, R = 1, 32, 1, 4096, 192, 64
    return {
        "q": _w((lambda *s: torch.randn(*s, dtype=torch.bfloat16) * 0.8)(B, H, Sq, Dh)),
        "k": _w((lambda *s: torch.randn(*s, dtype=torch.bfloat16) * 0.8)(B, H, Skv, Dh)),
        "v": _w((lambda *s: torch.randn(*s, dtype=torch.bfloat16) * 0.05)(B, H, Skv, Dh)),
        "e_proj": _w((lambda *s: torch.randn(*s, dtype=torch.bfloat16) * 0.8)(R, Skv) * (Skv ** -0.5)),
        "f_proj": _w((lambda *s: torch.randn(*s, dtype=torch.bfloat16) * 0.05)(R, Skv) * (Skv ** -0.5)),
    }

def reference(q, k, v, e_proj, f_proj):
    B, H, Sq, Dh = q.shape
    kp = torch.einsum("rn,bhnd->bhrd", e_proj, k)
    vp = torch.einsum("rn,bhnd->bhrd", f_proj, v)
    scores = torch.einsum("bhqd,bhrd->bhqr", q, kp) * (Dh ** -0.5)
    p = _softmax(scores, axis=-1)
    o = torch.einsum("bhqr,bhrd->bhqd", p, vp)
    return o
```

```cpp
#include <cuda_runtime.h>
#include <cuda_bf16.h>
#include <stdint.h>

namespace lf {

constexpr int H = 32, SKV = 4096, DH = 192;
constexpr int NCTA = 128;
constexpr int NC = 16;
constexpr int NG = 8;
constexpr int HPC = 4;
constexpr int ROWB = DH * 2;
constexpr int STAGE_B = 64 * ROWB;
constexpr int NS = 8;
constexpr int NSTAGE = 32;
constexpr int NTHREADS = 384;

constexpr int OFF_W = NS * STAGE_B;
constexpr int OFF_P = OFF_W + 8192;
constexpr int OFF_S = OFF_P + 1024;
constexpr int OFF_Q = OFF_S + 4096;
constexpr int OFF_BAR = OFF_Q + 6144;
constexpr int B_FULL = 0, B_EMPTY = 32, B_S = 56, B_P = 60, B_W = 64, B_O = 68, NBAR = 77;
constexpr int SMEM_BYTES = OFF_BAR + NBAR * 8;

constexpr int SPIN_LIMIT = 1 << 22;

__device__ float2 g_sc[H * NC * 32];
__device__ float2 g_op[H * 3 * NC * 32];
__device__ unsigned g_cnt[NG * 32];
__device__ unsigned g_epoch[NCTA * 16];

__device__ __forceinline__ uint32_t smem_u32(const void* p) { return (uint32_t)__cvta_generic_to_shared(p); }
__device__ __forceinline__ void mbar_init(uint32_t bar, uint32_t cnt) {
    asm volatile("mbarrier.init.shared::cta.b64 [%0], %1;" :: "r"(bar), "r"(cnt) : "memory");
}
__device__ __forceinline__ void mbar_expect_tx(uint32_t bar, uint32_t bytes) {
    asm volatile("mbarrier.arrive.expect_tx.shared::cta.b64 _, [%0], %1;" :: "r"(bar), "r"(bytes) : "memory");
}
__device__ __forceinline__ void mbar_arrive(uint32_t bar) {
    asm volatile("mbarrier.arrive.shared::cta.b64 _, [%0];" :: "r"(bar) : "memory");
}
__device__ __forceinline__ void mbar_arrive_n(uint32_t bar, uint32_t n) {
    asm volatile("mbarrier.arrive.shared::cta.b64 _, [%0], %1;" :: "r"(bar), "r"(n) : "memory");
}
__device__ __forceinline__ void mbar_wait(uint32_t bar) {
    asm volatile("{\n.reg .pred p;\n.reg .u32 n;\nmov.u32 n, 0;\n"
                 "LF_WAIT_%=:\n"
                 "mbarrier.try_wait.parity.shared::cta.b64 p, [%0], 0;\n"
                 "@p bra LF_DONE_%=;\n"
                 "add.u32 n, n, 1;\n"
                 "setp.lt.u32 p, n, %1;\n"
                 "@p bra LF_WAIT_%=;\n"
                 "trap;\n"
                 "LF_DONE_%=:\n}"
                 :: "r"(bar), "n"(SPIN_LIMIT) : "memory");
}
__device__ __forceinline__ void bulk_g2s(uint32_t dst, const void* src, uint32_t bytes, uint32_t bar) {
    const uint64_t evict_first = 0x12F0000000000000ull;
    asm volatile("cp.async.bulk.shared::cluster.global.mbarrier::complete_tx::bytes.L2::cache_hint [%0], [%1], %2, [%3], %4;"
                 :: "r"(dst), "l"(src), "r"(bytes), "r"(bar), "l"(evict_first) : "memory");
}
__device__ __forceinline__ bool elect() {
    uint32_t p;
    asm volatile("{\n.reg .pred P;\nelect.sync _|P, 0xffffffff;\nselp.u32 %0, 1, 0, P;\n}" : "=r"(p));
    return p;
}
__device__ __forceinline__ void mma(float (&d)[4], uint32_t a0, uint32_t a1, uint32_t a2, uint32_t a3, uint32_t b0, uint32_t b1) {
    asm volatile("mma.sync.aligned.m16n8k16.row.col.f32.bf16.bf16.f32 {%0,%1,%2,%3}, {%4,%5,%6,%7}, {%8,%9}, {%0,%1,%2,%3};"
                 : "+f"(d[0]), "+f"(d[1]), "+f"(d[2]), "+f"(d[3])
                 : "r"(a0), "r"(a1), "r"(a2), "r"(a3), "r"(b0), "r"(b1));
}
__device__ __forceinline__ uint4 lds128(uint32_t addr) {
    uint4 v;
    asm volatile("ld.shared.v4.u32 {%0,%1,%2,%3}, [%4];" : "=r"(v.x), "=r"(v.y), "=r"(v.z), "=r"(v.w) : "r"(addr) : "memory");
    return v;
}
__device__ __forceinline__ void sts128(uint32_t addr, uint4 v) {
    asm volatile("st.shared.v4.u32 [%0], {%1,%2,%3,%4};" :: "r"(addr), "r"(v.x), "r"(v.y), "r"(v.z), "r"(v.w) : "memory");
}
__device__ __forceinline__ void sts64(uint32_t addr, uint32_t x, uint32_t y) {
    asm volatile("st.shared.v2.u32 [%0], {%1,%2};" :: "r"(addr), "r"(x), "r"(y) : "memory");
}
__device__ __forceinline__ float2 lds64f(uint32_t addr) {
    float2 v;
    asm volatile("ld.shared.v2.f32 {%0,%1}, [%2];" : "=f"(v.x), "=f"(v.y) : "r"(addr) : "memory");
    return v;
}
__device__ __forceinline__ uint4 ldsm4t(uint32_t addr) {
    uint4 v;
    asm volatile("ldmatrix.sync.aligned.m8n8.x4.trans.shared.b16 {%0,%1,%2,%3}, [%4];"
                 : "=r"(v.x), "=r"(v.y), "=r"(v.z), "=r"(v.w) : "r"(addr) : "memory");
    return v;
}
__device__ __forceinline__ uint4 ldg128(const void* p) {
    uint4 v;
    asm volatile("ld.global.nc.v4.u32 {%0,%1,%2,%3}, [%4];" : "=r"(v.x), "=r"(v.y), "=r"(v.z), "=r"(v.w) : "l"(p));
    return v;
}
__device__ __forceinline__ uint2 ld_relaxed(const float2* p) {
    uint2 v;
    asm volatile("{\n.reg .b64 u;\nld.relaxed.gpu.global.b64 u, [%2];\nmov.b64 {%0,%1}, u;\n}"
                 : "=r"(v.x), "=r"(v.y) : "l"(p) : "memory");
    return v;
}
__device__ __forceinline__ void reload_if_stale(uint2& v, const float2* p, uint32_t tag) {
    asm volatile("{\n.reg .pred s;\n.reg .b32 x;\n.reg .b64 u;\n"
                 "lop3.b32 x, %0, %3, 1, 0x28;\nsetp.ne.u32 s, x, 0;\n"
                 "mov.b64 u, {%0,%1};\n@s ld.relaxed.gpu.global.b64 u, [%2];\nmov.b64 {%0,%1}, u;\n}"
                 : "+r"(v.x), "+r"(v.y) : "l"(p), "r"(tag) : "memory");
}
__device__ __forceinline__ void st_tagged(float2* p, float x, float y, uint32_t tag) {
    const uint32_t a = (__float_as_uint(x) & ~1u) | tag;
    asm volatile("{\n.reg .b64 u;\nmov.b64 u, {%1,%2};\nst.relaxed.gpu.global.b64 [%0], u;\n}"
                 :: "l"(p), "r"(a), "r"(__float_as_uint(y)) : "memory");
}
template <int LUT>
__device__ __forceinline__ uint32_t lop3(uint32_t a, uint32_t b, uint32_t c) {
    uint32_t r;
    asm("lop3.b32 %0, %1, %2, %3, %4;" : "=r"(r) : "r"(a), "r"(b), "r"(c), "n"(LUT));
    return r;
}
__device__ __forceinline__ float fsel(float a, float b, uint32_t pick_b) {
    float r;
    asm("{\n.reg .pred s;\nsetp.ne.u32 s, %3, 0;\nselp.f32 %0, %2, %1, s;\n}" : "=f"(r) : "f"(a), "f"(b), "r"(pick_b));
    return r;
}
__device__ __forceinline__ uint32_t pack_hi(float x, float y) {
    uint32_t r;
    asm("cvt.rn.bf16x2.f32 %0, %1, %2;" : "=r"(r) : "f"(y), "f"(x));
    return r;
}
__device__ __forceinline__ void split2(float x, float y, uint32_t& hi, uint32_t& lo) {
    hi = pack_hi(x, y);
    lo = pack_hi(x - __uint_as_float(hi << 16), y - __uint_as_float(hi & 0xffff0000u));
}
__device__ __forceinline__ uint32_t word(const uint4& v, int i) { return i == 0 ? v.x : i == 1 ? v.y : i == 2 ? v.z : v.w; }

__device__ __forceinline__ float2 pick_tile(const float (&d)[8][4], int g) {
    float x[8], y[8];
#pragma unroll
    for (int i = 0; i < 8; i++) { x[i] = d[i][0] + d[i][2]; y[i] = d[i][1] + d[i][3]; }
#pragma unroll
    for (int i = 0; i < 4; i++) { x[i] = fsel(x[i], x[i + 4], g & 4); y[i] = fsel(y[i], y[i + 4], g & 4); }
#pragma unroll
    for (int i = 0; i < 2; i++) { x[i] = fsel(x[i], x[i + 2], g & 2); y[i] = fsel(y[i], y[i + 2], g & 2); }
    return make_float2(fsel(x[0], x[1], g & 1), fsel(y[0], y[1], g & 1));
}

__device__ __forceinline__ void gather_issue(uint2 (&v)[NC], const float2* base) {
#pragma unroll
    for (int i = 0; i < NC; i++) v[i] = ld_relaxed(base + i * 32);
}
__device__ __forceinline__ float2 gather_finish(uint2 (&v)[NC], const float2* base, uint32_t tag) {
#pragma unroll 1
    for (int it = 0;; it++) {
        uint32_t m[8];
#pragma unroll
        for (int i = 0; i < 8; i++) m[i] = lop3<0x7E>(v[2 * i].x, v[2 * i + 1].x, tag);
        const uint32_t bad = lop3<0xFE>(lop3<0xFE>(m[0], m[1], m[2]), lop3<0xFE>(m[3], m[4], m[5]), m[6] | m[7]);
        if (!__any_sync(0xffffffffu, bad & 1)) break;
        if (it > SPIN_LIMIT) __trap();
#pragma unroll
        for (int i = 0; i < NC; i++) reload_if_stale(v[i], base + i * 32, tag);
    }
    float x[NC], y[NC];
#pragma unroll
    for (int i = 0; i < NC; i++) { x[i] = __uint_as_float(v[i].x); y[i] = __uint_as_float(v[i].y); }
#pragma unroll
    for (int i = 0; i < 8; i++) { x[i] += x[i + 8]; y[i] += y[i + 8]; }
#pragma unroll
    for (int i = 0; i < 4; i++) { x[i] += x[i + 4]; y[i] += y[i + 4]; }
    return make_float2((x[0] + x[2]) + (x[1] + x[3]), (y[0] + y[2]) + (y[1] + y[3]));
}

template <int DEPTH, int GATHER_AT>
__global__ void __launch_bounds__(NTHREADS, 1)
linformer_decode_kernel(const __nv_bfloat16* __restrict__ q, const __nv_bfloat16* __restrict__ k,
                        const __nv_bfloat16* __restrict__ v, const __nv_bfloat16* __restrict__ e,
                        const __nv_bfloat16* __restrict__ f, __nv_bfloat16* __restrict__ out) {
    extern __shared__ __align__(1024) unsigned char smem[];
    const uint32_t sb = smem_u32(smem);
    const uint32_t bars = sb + OFF_BAR;
    const int warp = __shfl_sync(0xffffffffu, threadIdx.x >> 5, 0), lane = threadIdx.x & 31;
    const int grp = blockIdx.x & (NG - 1), c = blockIdx.x >> 3;
    const int g = lane >> 2, t = lane & 3;

    if (warp == 0) {
        const size_t cta_off = (size_t)(grp * SKV + c * 256) * ROWB;
        const char* kb = (const char*)k + cta_off;
        const char* vb = (const char*)v + cta_off;
        auto issue = [&](int s) {
            const char* src = ((s & 16) ? vb : kb) + (size_t)(((s >> 2) & 3) * NG * SKV + (s & 3) * 64) * ROWB;
            mbar_expect_tx(bars + (B_FULL + s) * 8, STAGE_B);
            bulk_g2s(sb + (s & (NS - 1)) * STAGE_B, src, STAGE_B, bars + (B_FULL + s) * 8);
        };
        const bool leader = elect();
        if (leader) {
#pragma unroll
            for (int s = 0; s < DEPTH; s++) { mbar_init(bars + (B_FULL + s) * 8, 1); issue(s); }
        }
        __syncthreads();
        if (leader) {
#pragma unroll 1
            for (int s = DEPTH; s < NSTAGE; s++) {
                mbar_wait(bars + (B_FULL + s - DEPTH) * 8);
                if (s >= NS) mbar_wait(bars + (B_EMPTY + s - NS) * 8);
                issue(s);
            }
        }
        return;
    }

    unsigned* epoch_ptr = g_epoch + blockIdx.x * 16 + warp;
    const uint32_t epoch = *(volatile unsigned*)epoch_ptr;

    if (warp < 4) {
        const int blk = warp - 1;
        if (elect()) {
            if (blk == 0) {
#pragma unroll
                for (int s = DEPTH; s < NSTAGE; s++) mbar_init(bars + (B_FULL + s) * 8, 1);
            } else if (blk == 1) {
#pragma unroll
                for (int s = 0; s < NSTAGE - NS; s++) mbar_init(bars + (B_EMPTY + s) * 8, 3);
            } else {
#pragma unroll
                for (int j = 0; j < 4; j++) {
                    mbar_init(bars + (B_S + j) * 8, 4);
                    mbar_init(bars + (B_P + j) * 8, 1);
                    mbar_init(bars + (B_W + j) * 8, 4);
                }
#pragma unroll
                for (int j = 0; j < 9; j++) mbar_init(bars + (B_O + j) * 8, 1);
            }
        }
        __syncthreads();
        const uint32_t tag = (epoch + 1) & 1;
        if (lane == 0) *epoch_ptr = epoch + 1;

        const int mat = lane >> 3, mi = lane & 7;
        uint32_t off[4];
#pragma unroll
        for (int jp = 0; jp < 4; jp++)
            off[jp] = sb + ((mat & 1) * 8 + mi) * ROWB + blk * 128 + (((2 * jp + (mat >> 1)) ^ mi) << 4);
        const uint32_t amask = (t == (g >> 1)) ? 0xffffffffu : 0u;

#pragma unroll 1
        for (int j = 0; j < HPC; j++) {
            float acc[8][4];
#pragma unroll
            for (int i = 0; i < 8; i++) { acc[i][0] = acc[i][1] = acc[i][2] = acc[i][3] = 0.f; }
            mbar_wait(bars + (B_W + j) * 8);
#pragma unroll 1
            for (int sub = 0; sub < 4; sub++) {
                const int s = 16 + j * 4 + sub;
                uint4 a[4];
#pragma unroll
                for (int ks = 0; ks < 4; ks++) {
                    a[ks] = lds128(sb + OFF_W + ((j * 4 + sub) * 4 + ks) * 128 + g * 16);
                    a[ks].x &= amask; a[ks].y &= amask; a[ks].z &= amask; a[ks].w &= amask;
                }
                const uint32_t slot = (s & (NS - 1)) * STAGE_B;
                mbar_wait(bars + (B_FULL + s) * 8);
#pragma unroll
                for (int ks = 0; ks < 4; ks++) {
#pragma unroll
                    for (int jp = 0; jp < 4; jp++) {
                        const uint4 b = ldsm4t(off[jp] + slot + ks * 16 * ROWB);
                        mma(acc[2 * jp], a[ks].x, a[ks].y, a[ks].z, a[ks].w, b.x, b.y);
                        mma(acc[2 * jp + 1], a[ks].x, a[ks].y, a[ks].z, a[ks].w, b.z, b.w);
                    }
                }
                if (s < NSTAGE - NS) {
                    __syncwarp();
                    if (lane == 0) mbar_arrive(bars + (B_EMPTY + s) * 8);
                }
            }
            float x[8], y[8];
#pragma unroll
            for (int i = 0; i < 8; i++) { x[i] = acc[i][0] + acc[i][2]; y[i] = acc[i][1] + acc[i][3]; }
#pragma unroll
            for (int i = 0; i < 4; i++) {
                x[i] += __shfl_xor_sync(0xffffffffu, x[i + 4], 16);
                y[i] += __shfl_xor_sync(0xffffffffu, y[i + 4], 16);
            }
#pragma unroll
            for (int i = 0; i < 2; i++) {
                x[i] += __shfl_xor_sync(0xffffffffu, x[i + 2], 8);
                y[i] += __shfl_xor_sync(0xffffffffu, y[i + 2], 8);
            }
            x[0] += __shfl_xor_sync(0xffffffffu, x[1], 4);
            y[0] += __shfl_xor_sync(0xffffffffu, y[1], 4);
            const int h = j * NG + grp;
            float2* part = g_op + (h * 3 + blk) * NC * 32 + lane;
            st_tagged(part + c * 32, x[0], y[0], tag);
            if (j < HPC - 1) {
                __syncwarp();
                if (lane == 0) mbar_arrive(bars + (B_O + j * 3 + blk) * 8);
            } else {
                unsigned old = 0;
                if (lane == 0) old = atomicInc(g_cnt + grp * 32 + j * 3 + blk, NC - 1);
                uint2 pv[NC];
                gather_issue(pv, part);
                old = __shfl_sync(0xffffffffu, old, 0);
                if (old == NC - 1) {
                    const float2 o = gather_finish(pv, part, tag);
                    *(uint32_t*)(out + h * DH + blk * 64 + 2 * lane) = pack_hi(o.x, o.y);
                }
            }
        }
    } else if (warp < 8) {
        const int w = warp - 4;
        uint4 ea[8], eb[8];
        const __nv_bfloat16* ep = e + (size_t)g * SKV + c * 256 + w * 64 + t * 16;
        uint4 qv[3];
#pragma unroll
        for (int i = 0; i < 3; i++) {
            const int x = lane + 32 * i, j = x / 24;
            qv[i] = ldg128(q + (j * NG + grp) * DH + (x - j * 24) * 8);
        }
#pragma unroll
        for (int i = 0; i < 8; i++) { ea[i] = ldg128(ep + (size_t)i * 8 * SKV); eb[i] = ldg128(ep + (size_t)i * 8 * SKV + 8); }
        __syncthreads();
        const uint32_t qs = sb + OFF_Q + w * 1536;
#pragma unroll
        for (int i = 0; i < 3; i++) sts128(qs + (lane + 32 * i) * 16, qv[i]);
        __syncwarp();
        const uint32_t tag = (epoch + 1) & 1;
        if (lane == 0) *epoch_ptr = epoch + 1;

        const uint32_t kofs0 = sb + g * 8 * ROWB + t * 16 + (g & 1) * 64;
        const uint32_t kofs1 = sb + g * 8 * ROWB + t * 16 + ((g & 1) ^ 1) * 64;
#pragma unroll 1
        for (int j = 0; j < HPC; j++) {
            const int s = j * 4 + w;
            uint4 qf[6];
#pragma unroll
            for (int i = 0; i < 6; i++) qf[i] = lds128(qs + j * ROWB + (t + 4 * i) * 16);
            const uint32_t slot = (s & (NS - 1)) * STAGE_B;
            mbar_wait(bars + (B_FULL + s) * 8);
            float s0[8], s1[8];
#pragma unroll
            for (int tp = 0; tp < 8; tp += 4) {
                float d[4][4];
#pragma unroll
                for (int u = 0; u < 4; u++) { d[u][0] = d[u][1] = d[u][2] = d[u][3] = 0.f; }
#pragma unroll
                for (int i = 0; i < 6; i++) {
#pragma unroll
                    for (int u = 0; u < 4; u++) {
                        const uint4 kv = lds128(((i & 1) ? kofs1 : kofs0) + slot + (tp + u) * ROWB + (i >> 1) * 128);
                        mma(d[u], qf[i].x, qf[i ^ 1].x, qf[i].y, qf[i ^ 1].y, kv.x, kv.y);
                        mma(d[u], qf[i].z, qf[i ^ 1].z, qf[i].w, qf[i ^ 1].w, kv.z, kv.w);
                    }
                }
#pragma unroll
                for (int u = 0; u < 4; u++) { s0[tp + u] = d[u][0]; s1[tp + u] = d[u][3]; }
            }
            __syncwarp();
            if (lane == 0) mbar_arrive_n(bars + (B_EMPTY + s) * 8, 3);

            float d2[8][4];
#pragma unroll
            for (int i = 0; i < 8; i++) { d2[i][0] = d2[i][1] = d2[i][2] = d2[i][3] = 0.f; }
#pragma unroll
            for (int ks = 0; ks < 4; ks++) {
                uint32_t a0, a1, a2, a3;
                split2(s0[2 * ks], s0[2 * ks + 1], a0, a1);
                split2(s1[2 * ks], s1[2 * ks + 1], a2, a3);
#pragma unroll
                for (int i = 0; i < 8; i++) mma(d2[i], a0, a1, a2, a3, word(ea[i], ks), word(eb[i], ks));
            }
            const float2 sc = pick_tile(d2, g);
            sts64(sb + OFF_S + (j * 4 + w) * 256 + lane * 8, __float_as_uint(sc.x), __float_as_uint(sc.y));
            __syncwarp();
            if (lane == 0) mbar_arrive(bars + (B_S + j) * 8);
            if (w == 3) {
                mbar_wait(bars + (B_S + j) * 8);
                const float2 p0 = lds64f(sb + OFF_S + (j * 4 + 0) * 256 + lane * 8);
                const float2 p1 = lds64f(sb + OFF_S + (j * 4 + 1) * 256 + lane * 8);
                const float2 p2 = lds64f(sb + OFF_S + (j * 4 + 2) * 256 + lane * 8);
                st_tagged(g_sc + ((j * NG + grp) * NC + c) * 32 + lane,
                          (p0.x + p1.x) + (p2.x + sc.x), (p0.y + p1.y) + (p2.y + sc.y), tag);
            }
        }
        if (w < 3) {
#pragma unroll 1
            for (int j = 0; j < HPC - 1; j++) {
                mbar_wait(bars + (B_O + j * 3 + w) * 8);
                unsigned old = 0;
                if (lane == 0) old = atomicInc(g_cnt + grp * 32 + j * 3 + w, NC - 1);
                old = __shfl_sync(0xffffffffu, old, 0);
                if (old == NC - 1) {
                    const int h = j * NG + grp;
                    const float2* part = g_op + (h * 3 + w) * NC * 32 + lane;
                    uint2 pv[NC];
                    gather_issue(pv, part);
                    const float2 o = gather_finish(pv, part, tag);
                    *(uint32_t*)(out + h * DH + w * 64 + 2 * lane) = pack_hi(o.x, o.y);
                }
            }
        }
    } else {
        const int w = warp - 8;
        uint4 fr[16];
        const __nv_bfloat16* fp = f + (size_t)(2 * t) * SKV + c * 256 + w * 64 + g * 8;
#pragma unroll
        for (int i = 0; i < 16; i++) fr[i] = ldg128(fp + (size_t)((i >> 1) * 8 + (i & 1)) * SKV);
        __syncthreads();
        const uint32_t tag = (epoch + 1) & 1;
        if (lane == 0) *epoch_ptr = epoch + 1;
        uint32_t fb[8][8];
#pragma unroll
        for (int i = 0; i < 8; i++)
#pragma unroll
            for (int x = 0; x < 8; x++)
                fb[i][x] = __byte_perm(word(fr[2 * x], i >> 1), word(fr[2 * x + 1], i >> 1), (i & 1) ? 0x7632 : 0x5410);

#pragma unroll 1
        for (int j = 0; j < HPC; j++) {
            if (j == w) {
                mbar_wait(bars + (B_FULL + GATHER_AT + 4 * j) * 8);
                const float2* part = g_sc + (j * NG + grp) * NC * 32 + lane;
                uint2 pv[NC];
                gather_issue(pv, part);
                float2 sc = gather_finish(pv, part, tag);
                const float scale = 0.07216878364870322f;
                sc.x *= scale; sc.y *= scale;
                float m = fmaxf(sc.x, sc.y);
#pragma unroll
                for (int o = 16; o > 0; o >>= 1) m = fmaxf(m, __shfl_xor_sync(0xffffffffu, m, o));
                const float e0 = expf(sc.x - m), e1 = expf(sc.y - m);
                float sum = e0 + e1;
#pragma unroll
                for (int o = 16; o > 0; o >>= 1) sum += __shfl_xor_sync(0xffffffffu, sum, o);
                uint32_t hi, lo;
                split2(e0 / sum, e1 / sum, hi, lo);
                sts64(sb + OFF_P + j * 256 + (g >> 1) * 64 + t * 16 + (g & 1) * 8, hi, lo);
                __syncwarp();
                if (lane == 0) mbar_arrive(bars + (B_P + j) * 8);
            }
            mbar_wait(bars + (B_P + j) * 8);
            float d[8][4];
#pragma unroll
            for (int i = 0; i < 8; i++) { d[i][0] = d[i][1] = d[i][2] = d[i][3] = 0.f; }
#pragma unroll
            for (int ks = 0; ks < 4; ks++) {
                const uint4 a = lds128(sb + OFF_P + j * 256 + ks * 64 + t * 16);
#pragma unroll
                for (int i = 0; i < 8; i++) mma(d[i], a.x, a.y, a.z, a.w, fb[i][2 * ks], fb[i][2 * ks + 1]);
            }
            const float2 wv = pick_tile(d, g);
            uint32_t hi, lo;
            split2(wv.x, wv.y, hi, lo);
            const int sh = (g & 1) * 16;
            sts128(sb + OFF_W + ((j * 4 + w) * 4 + t) * 128 + g * 16,
                   make_uint4((hi & 0xffffu) << sh, (lo & 0xffffu) << sh, (hi >> 16) << sh, (lo >> 16) << sh));
            __syncwarp();
            if (lane == 0) mbar_arrive(bars + (B_W + j) * 8);
        }
    }
}

}

extern "C" void kernel_launch(void* const* d_in, const int* in_sizes, int n_in, void* d_out, int out_size) {
    auto kern = lf::linformer_decode_kernel<4, 9>;
    cudaFuncSetAttribute(kern, cudaFuncAttributeMaxDynamicSharedMemorySize, lf::SMEM_BYTES);
    kern<<<lf::NCTA, lf::NTHREADS, lf::SMEM_BYTES>>>(
        (const __nv_bfloat16*)d_in[0], (const __nv_bfloat16*)d_in[1], (const __nv_bfloat16*)d_in[2],
        (const __nv_bfloat16*)d_in[3], (const __nv_bfloat16*)d_in[4], (__nv_bfloat16*)d_out);
}
```

```cpp
#include <cuda.h>
#include <cuda_runtime.h>
#include <cuda_bf16.h>
#include <stdint.h>

namespace lf {

constexpr int H = 32, SKV = 4096, DH = 192;
constexpr int NCTA = 128;
constexpr int NC = 16;
constexpr int NG = 8;
constexpr int HPC = 4;
constexpr int ROWB = DH * 2;
constexpr int STAGE_B = 64 * ROWB;
constexpr int NS = 8;
constexpr int NSTAGE = 32;
constexpr int NV = 6;
constexpr int NTHREADS = (1 + NV + 4 + 1) * 32;

constexpr int TILE_B = 64 * 128;
constexpr int OFF_X = NS * STAGE_B;
constexpr int OFF_W = OFF_X + 2 * TILE_B;
constexpr int OFF_P = OFF_W + 4096;
constexpr int OFF_S = OFF_P + 1024;
constexpr int OFF_Q = OFF_S + 4096;
constexpr int OFF_O = OFF_Q + 1536;
constexpr int OFF_BAR = OFF_O + 2304;
constexpr int B_FULL = 0, B_FREE = 32 - 6, B_S = 58, B_P = 62, B_W = 66, B_O = 70, B_E = 73, B_F = 74, B_TAG = 75, B_LAST = 76, NBAR = 93;
constexpr int OFF_TAG = OFF_BAR + 92 * 8;
constexpr int SMEM_BYTES = OFF_BAR + NBAR * 8;

constexpr int SPIN_LIMIT = 1 << 22;

constexpr int ACC_PITCH = 4224;
struct Scratch {
    float2 sc[H * NC * 32];
    unsigned char acc[NG * 36 * ACC_PITCH];
    unsigned epoch[NCTA];
};
__device__ Scratch g_scratch;

#define TRACE(id)
#define TRACE_DUMP(lo, hi)

__device__ __forceinline__ uint32_t smem_u32(const void* p) { return (uint32_t)__cvta_generic_to_shared(p); }
__device__ __forceinline__ void mbar_init(uint32_t bar, uint32_t cnt) {
    asm volatile("mbarrier.init.shared::cta.b64 [%0], %1;" :: "r"(bar), "r"(cnt) : "memory");
}
__device__ __forceinline__ void mbar_expect_tx(uint32_t bar, uint32_t bytes) {
    asm volatile("mbarrier.arrive.expect_tx.shared::cta.b64 _, [%0], %1;" :: "r"(bar), "r"(bytes) : "memory");
}
__device__ __forceinline__ void mbar_arrive(uint32_t bar) {
    asm volatile("mbarrier.arrive.shared::cta.b64 _, [%0];" :: "r"(bar) : "memory");
}
__device__ __forceinline__ void mbar_arrive_n(uint32_t bar, uint32_t n) {
    asm volatile("mbarrier.arrive.shared::cta.b64 _, [%0], %1;" :: "r"(bar), "r"(n) : "memory");
}
__device__ __forceinline__ void mbar_wait(uint32_t bar) {
    asm volatile("{\n.reg .pred p;\n.reg .u32 n;\nmov.u32 n, 0;\n"
                 "LF_WAIT_%=:\n"
                 "mbarrier.try_wait.parity.shared::cta.b64 p, [%0], 0;\n"
                 "@p bra LF_DONE_%=;\n"
                 "add.u32 n, n, 1;\n"
                 "setp.lt.u32 p, n, %1;\n"
                 "@p bra LF_WAIT_%=;\n"
                 "trap;\n"
                 "LF_DONE_%=:\n}"
                 :: "r"(bar), "n"(SPIN_LIMIT) : "memory");
}
__device__ __forceinline__ void mbar_spin(uint32_t bar) {
    asm volatile("{\n.reg .pred p;\n.reg .u32 n;\nmov.u32 n, 0;\n"
                 "LF_SPIN_%=:\n"
                 "mbarrier.test_wait.parity.shared::cta.b64 p, [%0], 0;\n"
                 "@p bra LF_SDONE_%=;\n"
                 "add.u32 n, n, 1;\n"
                 "setp.lt.u32 p, n, %1;\n"
                 "@p bra LF_SPIN_%=;\n"
                 "trap;\n"
                 "LF_SDONE_%=:\n}"
                 :: "r"(bar), "n"(SPIN_LIMIT * 64) : "memory");
}
__device__ __forceinline__ void bulk_g2s(uint32_t dst, const void* src, uint32_t bytes, uint32_t bar) {
    const uint64_t evict_first = 0x12F0000000000000ull;
    asm volatile("cp.async.bulk.shared::cluster.global.mbarrier::complete_tx::bytes.L2::cache_hint [%0], [%1], %2, [%3], %4;"
                 :: "r"(dst), "l"(src), "r"(bytes), "r"(bar), "l"(evict_first) : "memory");
}
__device__ __forceinline__ void tile_g2s(uint32_t dst, const CUtensorMap* map, int n0, uint32_t bar) {
    asm volatile("cp.async.bulk.tensor.2d.shared::cluster.global.mbarrier::complete_tx::bytes [%0], [%1, {%2, %3}], [%4];"
                 :: "r"(dst), "l"(map), "r"(n0), "r"(0), "r"(bar) : "memory");
}
__device__ __forceinline__ void lines_g2s(uint32_t dst, const CUtensorMap* map, int line0, uint32_t bar) {
    const uint64_t evict_first = 0x12F0000000000000ull;
    asm volatile("cp.async.bulk.tensor.2d.shared::cluster.global.mbarrier::complete_tx::bytes.L2::cache_hint [%0], [%1, {%2, %3}], [%4], %5;"
                 :: "r"(dst), "l"(map), "r"(0), "r"(line0), "r"(bar), "l"(evict_first) : "memory");
}
__device__ __forceinline__ bool elect() {
    uint32_t p;
    asm volatile("{\n.reg .pred P;\nelect.sync _|P, 0xffffffff;\nselp.u32 %0, 1, 0, P;\n}" : "=r"(p));
    return p;
}
__device__ __forceinline__ void mma(float (&d)[4], uint32_t a0, uint32_t a1, uint32_t a2, uint32_t a3, uint32_t b0, uint32_t b1) {
    asm volatile("mma.sync.aligned.m16n8k16.row.col.f32.bf16.bf16.f32 {%0,%1,%2,%3}, {%4,%5,%6,%7}, {%8,%9}, {%0,%1,%2,%3};"
                 : "+f"(d[0]), "+f"(d[1]), "+f"(d[2]), "+f"(d[3])
                 : "r"(a0), "r"(a1), "r"(a2), "r"(a3), "r"(b0), "r"(b1));
}
__device__ __forceinline__ uint4 lds128(uint32_t addr) {
    uint4 v;
    asm volatile("ld.shared.v4.u32 {%0,%1,%2,%3}, [%4];" : "=r"(v.x), "=r"(v.y), "=r"(v.z), "=r"(v.w) : "r"(addr) : "memory");
    return v;
}
__device__ __forceinline__ void sts64(uint32_t addr, uint32_t x, uint32_t y) {
    asm volatile("st.shared.v2.u32 [%0], {%1,%2};" :: "r"(addr), "r"(x), "r"(y) : "memory");
}
__device__ __forceinline__ void sts32(uint32_t addr, uint32_t x) {
    asm volatile("st.shared.u32 [%0], %1;" :: "r"(addr), "r"(x) : "memory");
}
__device__ __forceinline__ uint32_t lds32(uint32_t addr) {
    uint32_t v;
    asm volatile("ld.shared.u32 %0, [%1];" : "=r"(v) : "r"(addr) : "memory");
    return v;
}
__device__ __forceinline__ float2 lds64f(uint32_t addr) {
    float2 v;
    asm volatile("ld.shared.v2.f32 {%0,%1}, [%2];" : "=f"(v.x), "=f"(v.y) : "r"(addr) : "memory");
    return v;
}
__device__ __forceinline__ uint32_t wait_tag(uint32_t sb) {
    mbar_wait(sb + OFF_BAR + B_TAG * 8);
    uint32_t v;
    asm volatile("ld.shared.u32 %0, [%1];" : "=r"(v) : "r"(sb + OFF_TAG) : "memory");
    return v;
}
__device__ __forceinline__ uint4 ldsm4t(uint32_t addr) {
    uint4 v;
    asm volatile("ldmatrix.sync.aligned.m8n8.x4.trans.shared.b16 {%0,%1,%2,%3}, [%4];"
                 : "=r"(v.x), "=r"(v.y), "=r"(v.z), "=r"(v.w) : "r"(addr) : "memory");
    return v;
}
__device__ __forceinline__ uint2 ld_relaxed(const float2* p) {
    uint2 v;
    asm volatile("{\n.reg .b64 u;\nld.relaxed.gpu.global.b64 u, [%2];\nmov.b64 {%0,%1}, u;\n}"
                 : "=r"(v.x), "=r"(v.y) : "l"(p) : "memory");
    return v;
}
__device__ __forceinline__ void reload_if_stale(uint2& v, const float2* p, uint32_t tag) {
    asm volatile("{\n.reg .pred s;\n.reg .b32 x;\n.reg .b64 u;\n"
                 "lop3.b32 x, %0, %3, 1, 0x28;\nsetp.ne.u32 s, x, 0;\n"
                 "mov.b64 u, {%0,%1};\n@s ld.relaxed.gpu.global.b64 u, [%2];\nmov.b64 {%0,%1}, u;\n}"
                 : "+r"(v.x), "+r"(v.y) : "l"(p), "r"(tag) : "memory");
}
__device__ __forceinline__ void st_tagged(float2* p, float x, float y, uint32_t tag) {
    const uint32_t a = (__float_as_uint(x) & ~1u) | tag;
    asm volatile("{\n.reg .b64 u;\nmov.b64 u, {%1,%2};\nst.relaxed.gpu.global.b64 [%0], u;\n}"
                 :: "l"(p), "r"(a), "r"(__float_as_uint(y)) : "memory");
}
template <int LUT>
__device__ __forceinline__ uint32_t lop3(uint32_t a, uint32_t b, uint32_t c) {
    uint32_t r;
    asm("lop3.b32 %0, %1, %2, %3, %4;" : "=r"(r) : "r"(a), "r"(b), "r"(c), "n"(LUT));
    return r;
}
__device__ __forceinline__ float fsel(float a, float b, uint32_t pick_b) {
    float r;
    asm("{\n.reg .pred s;\nsetp.ne.u32 s, %3, 0;\nselp.f32 %0, %2, %1, s;\n}" : "=f"(r) : "f"(a), "f"(b), "r"(pick_b));
    return r;
}
__device__ __forceinline__ uint32_t pack_hi(float x, float y) {
    uint32_t r;
    asm("cvt.rn.bf16x2.f32 %0, %1, %2;" : "=r"(r) : "f"(y), "f"(x));
    return r;
}
__device__ __forceinline__ void split2(float x, float y, uint32_t& hi, uint32_t& lo) {
    hi = pack_hi(x, y);
    lo = pack_hi(x - __uint_as_float(hi << 16), y - __uint_as_float(hi & 0xffff0000u));
}
__device__ __forceinline__ uint32_t word(const uint4& v, int i) { return i == 0 ? v.x : i == 1 ? v.y : i == 2 ? v.z : v.w; }

template <int N, int STRIDE>
__device__ __forceinline__ void gather_issue(uint2 (&v)[N], const float2* base) {
#pragma unroll
    for (int i = 0; i < N; i++) v[i] = ld_relaxed(base + i * STRIDE);
}
template <int N, int STRIDE>
__device__ __forceinline__ float2 gather_finish(uint2 (&v)[N], const float2* base, uint32_t tag) {
#pragma unroll 1
    for (int it = 0;; it++) {
        uint32_t bad = 0;
#pragma unroll
        for (int i = 0; i < N; i += 4)
            bad = lop3<0xFE>(bad, lop3<0x7E>(v[i].x, v[i + 1].x, tag), lop3<0x7E>(v[i + 2].x, v[i + 3].x, tag));
        if (!__any_sync(0xffffffffu, bad & 1)) break;
        if (it > SPIN_LIMIT) __trap();
#pragma unroll
        for (int i = 0; i < N; i++) reload_if_stale(v[i], base + i * STRIDE, tag);
    }
    float x[N], y[N];
#pragma unroll
    for (int i = 0; i < N; i++) { x[i] = __uint_as_float(v[i].x); y[i] = __uint_as_float(v[i].y); }
    if (N == 16) {
#pragma unroll
        for (int i = 0; i < 8; i++) { x[i] += x[(i + 8) % N]; y[i] += y[(i + 8) % N]; }
    }
#pragma unroll
    for (int i = 0; i < 4; i++) { x[i] += x[i + 4]; y[i] += y[i + 4]; }
    return make_float2((x[0] + x[2]) + (x[1] + x[3]), (y[0] + y[2]) + (y[1] + y[3]));
}
__device__ __forceinline__ float4 accum4_issue(void* p, float x, float y, float z) {
    float4 r;
    asm volatile("atom.relaxed.gpu.global.add.v4.f32 {%0,%1,%2,%3}, [%4], {%5,%6,%7,%8};"
                 : "=f"(r.x), "=f"(r.y), "=f"(r.z), "=f"(r.w) : "l"(p), "f"(x), "f"(y), "f"(z), "f"(1.0f) : "memory");
    return r;
}
__device__ __forceinline__ void accum2(float2* p, float x, __nv_bfloat16* o) {
    float a, n;
    asm volatile("atom.relaxed.gpu.global.add.v2.f32 {%0,%1}, [%2], {%3,%4};" : "=f"(a), "=f"(n) : "l"(p), "f"(x), "f"(1.0f) : "memory");
    if (n == (float)(NC - 1)) {
        *o = __float2bfloat16(a + x);
        *p = make_float2(0.f, 0.f);
    }
}

template <int DEPTH, int GATHER_AT, int PRE, int F_AT, int MINI, int PIPE, int V2, int OPT, int D2, int SW>
__global__ void __launch_bounds__(NTHREADS, 1)
linformer_decode_kernel(const __nv_bfloat16* __restrict__ k, const __nv_bfloat16* __restrict__ q,
                        __nv_bfloat16* __restrict__ out, Scratch* __restrict__ scr,
                        const __grid_constant__ CUtensorMap vmap, const __grid_constant__ CUtensorMap emap,
                        const __grid_constant__ CUtensorMap fmap, const __grid_constant__ CUtensorMap vmini) {
    extern __shared__ __align__(1024) unsigned char smem[];
    const uint32_t sb = smem_u32(smem);
    const uint32_t bars = sb + OFF_BAR;
    const int grp = (OPT & 8) ? blockIdx.x >> 4 : blockIdx.x & (NG - 1), c = (OPT & 8) ? blockIdx.x & 15 : blockIdx.x >> 3;

    if (threadIdx.x < 32) {
        const bool leader = elect();
        const int row0 = grp * SKV + c * 256;
        auto issue_k = [&](int s) {
            const int row = row0 + (s >> 2) * NG * SKV + (s & 3) * 64;
            mbar_expect_tx(bars + (B_FULL + s) * 8, STAGE_B);
            bulk_g2s(sb + (s & (NS - 1)) * STAGE_B, (const char*)k + (size_t)row * ROWB, STAGE_B, bars + (B_FULL + s) * 8);
        };
        auto issue_v = [&](int s) {
            const int row = row0 + ((s >> 2) & 3) * NG * SKV + (s & 3) * 64;
            mbar_expect_tx(bars + (B_FULL + s) * 8, STAGE_B);
            lines_g2s(sb + (s & (NS - 1)) * STAGE_B, &vmap, row * 3, bars + (B_FULL + s) * 8);
        };
        auto issue_last = [&](int s) {
            const int row = row0 + 3 * NG * SKV + (s & 3) * 64;
#pragma unroll
            for (int m = 0; m < MINI; m++) {
                const uint32_t bar = bars + (B_LAST + (s & 3) * MINI + m) * 8;
                mbar_expect_tx(bar, STAGE_B / MINI);
                lines_g2s(sb + (s & (NS - 1)) * STAGE_B + m * (STAGE_B / MINI), MINI == 1 ? &vmap : &vmini, row * 3 + m * (192 / MINI), bar);
            }
        };
        if (leader) {
            if (OPT & 4) asm volatile("cp.async.bulk.prefetch.L2.global [%0], %1;" :: "l"((const char*)k + (size_t)row0 * ROWB), "r"(8192) : "memory");
#pragma unroll
            for (int s = 0; s < PRE; s++) { mbar_init(bars + (B_FULL + s) * 8, 1); issue_k(s); }
        }
        __syncthreads();
        if (leader) {
            TRACE(65);
            mbar_expect_tx(bars + B_E * 8, 4 * TILE_B + HPC * ROWB);
#pragma unroll
            for (int j = 0; j < HPC; j++) bulk_g2s(sb + OFF_Q + j * ROWB, q + (j * NG + grp) * DH, ROWB, bars + B_E * 8);
#pragma unroll
            for (int w = 0; w < 4; w++)
                tile_g2s(sb + (w < 3 ? 6 * STAGE_B + w * TILE_B : OFF_X), &emap, c * 256 + w * 64, bars + B_E * 8);
            TRACE(172);
#pragma unroll
            for (int s = PRE; s <= DEPTH; s++) {
                if (s == F_AT) {
                    mbar_expect_tx(bars + B_F * 8, 4 * TILE_B);
#pragma unroll
                    for (int w = 0; w < 4; w++)
                        tile_g2s(sb + (w < 3 ? 7 * STAGE_B + w * TILE_B : OFF_X + TILE_B), &fmap, c * 256 + w * 64, bars + B_F * 8);
                }
                if (s < DEPTH) issue_k(s);
            }
            TRACE(173);
#pragma unroll 1
            for (int s = DEPTH; s < NSTAGE; s++) {
                if (s >= 6) mbar_wait(bars + (B_FREE + s) * 8);
                const int dep = s - (s < SW ? DEPTH : D2);
                if (dep < 28) {
                    mbar_wait(bars + (B_FULL + dep) * 8);
                } else {
#pragma unroll
                    for (int m = 0; m < MINI; m++) mbar_wait(bars + (B_LAST + (dep - 28) * MINI + m) * 8);
                }
                TRACE(1 + s - DEPTH);
                if (s < 16) issue_k(s); else if (s < 28) issue_v(s); else issue_last(s);
                TRACE(33 + s);
            }
        }
        return;
    }

    const int warp = __shfl_sync(0xffffffffu, threadIdx.x >> 5, 0), lane = threadIdx.x & 31;
    const int g = lane >> 2, t = lane & 3;

    if (warp <= NV) {
        const int vw = warp - 1;
        if (elect()) {
            if (vw == 0) {
#pragma unroll
                for (int s = PRE; s < 16; s++) mbar_init(bars + (B_FULL + s) * 8, 1);
            } else if (vw == 1) {
#pragma unroll
                for (int s = 16; s < 28; s++) mbar_init(bars + (B_FULL + s) * 8, 1);
            } else if (vw == 2) {
#pragma unroll
                for (int s = 6; s < 19; s++) mbar_init(bars + (B_FREE + s) * 8, NV);
            } else if (vw == 3) {
#pragma unroll
                for (int s = 19; s < NSTAGE; s++) mbar_init(bars + (B_FREE + s) * 8, NV);
            } else if (vw == 4) {
#pragma unroll
                for (int j = 0; j < 4; j++) {
                    mbar_init(bars + (B_S + j) * 8, 4);
                    mbar_init(bars + (B_P + j) * 8, 1);
                    mbar_init(bars + (B_W + j) * 8, 4);
                }
            } else {
                asm volatile("prefetch.tensormap [%0];" :: "l"(&emap) : "memory");
                asm volatile("prefetch.tensormap [%0];" :: "l"(&fmap) : "memory");
                asm volatile("prefetch.tensormap [%0];" :: "l"(&vmap) : "memory");
                if (MINI > 1) asm volatile("prefetch.tensormap [%0];" :: "l"(&vmini) : "memory");
#pragma unroll
                for (int j = 0; j < 3; j++) mbar_init(bars + (B_O + j) * 8, NV);
                mbar_init(bars + B_E * 8, 1);
                mbar_init(bars + B_F * 8, 1);
                mbar_init(bars + B_TAG * 8, 1);
            }
        }
        __syncthreads();
        if (vw < 4) {
            const int w = vw;
            const uint32_t tile = sb + (w < 3 ? 6 * STAGE_B + w * TILE_B : OFF_X);
            const uint32_t qs = sb + OFF_Q;
            uint32_t ef[4][4][4];
            mbar_wait(bars + B_E * 8);
#pragma unroll
            for (int i = 0; i < 8; i++) {
                const uint4 ea = lds128(tile + (i * 8 + g) * 128 + (((2 * t) ^ g) << 4));
                const uint4 eb = lds128(tile + (i * 8 + g) * 128 + (((2 * t + 1) ^ g) << 4));
#pragma unroll
                for (int ks = 0; ks < 4; ks++) { ef[i >> 1][ks][i & 1] = word(ea, ks); ef[i >> 1][ks][2 + (i & 1)] = word(eb, ks); }
            }
            __syncwarp();
            if (lane == 0 && w < 3) mbar_arrive_n(bars + (B_FREE + 6) * 8, NV / 3);
            TRACE(66 + w);

            const uint32_t krow = sb + ((g & 3) * 16 + (g >> 2) * 8) * ROWB + t * 16;
            const uint32_t kofs0 = krow + (g & 1) * 64, kofs1 = krow + ((g & 1) ^ 1) * 64;
            const uint32_t qofs0 = qs + t * 16 + (g & 1) * 4 + (g & 2) * 32, qofs1 = qofs0 ^ 64;
            const uint32_t m0 = (g == t) ? 0xffffffffu : 0u, m1 = (g == t + 4) ? 0xffffffffu : 0u;
#pragma unroll 1
            for (int j = 0; j < HPC; j++) {
                const int s = j * 4 + w;
                uint32_t qf[6][2];
#pragma unroll
                for (int i = 0; i < 6; i++) {
                    qf[i][0] = lds32(((i & 1) ? qofs1 : qofs0) + j * ROWB + (i >> 1) * 128);
                    qf[i][1] = lds32(((i & 1) ? qofs1 : qofs0) + j * ROWB + (i >> 1) * 128 + 8);
                }
                const uint32_t slot = (s & (NS - 1)) * STAGE_B;
                mbar_wait(bars + (B_FULL + s) * 8);
                float d[8][4];
#pragma unroll
                for (int u = 0; u < 8; u++) { d[u][0] = d[u][1] = d[u][2] = d[u][3] = 0.f; }
#pragma unroll
                for (int i = 0; i < 6; i++)
#pragma unroll
                    for (int u = 0; u < 8; u++) {
                        const uint4 kv = lds128(((i & 1) ? kofs1 : kofs0) + slot + u * ROWB + (i >> 1) * 128);
                        mma(d[u], kv.x, kv.y, kv.z, kv.w, qf[i][0], qf[i][1]);
                    }
                __syncwarp();
                if (lane == 0) mbar_arrive_n(bars + (B_FREE + s + NS) * 8, NV);
                TRACE(112 + s);

                float d2[4][4];
#pragma unroll
                for (int i = 0; i < 4; i++) { d2[i][0] = d2[i][1] = d2[i][2] = d2[i][3] = 0.f; }
#pragma unroll
                for (int ks = 0; ks < 4; ks++) {
                    uint32_t hi, lo;
                    split2(d[2 * ks][0] + d[2 * ks][3], d[2 * ks + 1][0] + d[2 * ks + 1][3], hi, lo);
#pragma unroll
                    for (int i = 0; i < 4; i++) mma(d2[i], ef[i][ks][0], ef[i][ks][1], ef[i][ks][2], ef[i][ks][3], hi & m0, hi & m1);
#pragma unroll
                    for (int i = 0; i < 4; i++) mma(d2[i], ef[i][ks][0], ef[i][ks][1], ef[i][ks][2], ef[i][ks][3], lo & m0, lo & m1);
                }
                float x[4], y[4];
#pragma unroll
                for (int i = 0; i < 4; i++) { x[i] = d2[i][0] + d2[i][1]; y[i] = d2[i][2] + d2[i][3]; }
#pragma unroll
                for (int i = 0; i < 2; i++) {
                    x[i] = fsel(x[i], x[i + 2], t & 2) + __shfl_xor_sync(0xffffffffu, fsel(x[i + 2], x[i], t & 2), 2);
                    y[i] = fsel(y[i], y[i + 2], t & 2) + __shfl_xor_sync(0xffffffffu, fsel(y[i + 2], y[i], t & 2), 2);
                }
                const float sx = fsel(x[0], x[1], t & 1) + __shfl_xor_sync(0xffffffffu, fsel(x[1], x[0], t & 1), 1);
                const float sy = fsel(y[0], y[1], t & 1) + __shfl_xor_sync(0xffffffffu, fsel(y[1], y[0], t & 1), 1);
                sts32(sb + OFF_S + (j * 4 + w) * 256 + (16 * t + g) * 4, __float_as_uint(sx));
                sts32(sb + OFF_S + (j * 4 + w) * 256 + (16 * t + 8 + g) * 4, __float_as_uint(sy));
                __syncwarp();
                if (lane == 0) mbar_arrive(bars + (B_S + j) * 8);
                if (w == 3 && !(OPT & 64)) {
                    const uint32_t tag = wait_tag(sb);
                    mbar_wait(bars + (B_S + j) * 8);
                    const float2 p0 = lds64f(sb + OFF_S + (j * 4 + 0) * 256 + lane * 8);
                    const float2 p1 = lds64f(sb + OFF_S + (j * 4 + 1) * 256 + lane * 8);
                    const float2 p2 = lds64f(sb + OFF_S + (j * 4 + 2) * 256 + lane * 8);
                    const float2 p3 = lds64f(sb + OFF_S + (j * 4 + 3) * 256 + lane * 8);
                    st_tagged(scr->sc + ((j * NG + grp) * NC + c) * 32 + lane,
                              (p0.x + p1.x) + (p2.x + p3.x), (p0.y + p1.y) + (p2.y + p3.y), tag);
                    TRACE(130 + j);
                }
            }
        }

        const int mat = lane >> 3, mi = lane & 7;
        uint32_t off[2];
#pragma unroll
        for (int u = 0; u < 2; u++) {
            const int cc = vw * 4 + u * 2 + (mat & 1), blk = cc >> 3;
            off[u] = sb + ((mat >> 1) * 8 + mi) * ROWB + blk * 128 + (((cc & 7) ^ ((3 * mi + blk) & 7)) << 4);
        }
        const uint32_t wofs = sb + OFF_W + (g & 1) * 64 + t * 16;
        unsigned char* accp = scr->acc + (grp * 36 + 24 + vw * 2 + (lane >> 4)) * ACC_PITCH + (lane & 15) * 8;
        if (OPT & 128) accp = scr->acc + (grp * 36 + 24) * ACC_PITCH + 1024 + (vw * 32 + lane) * 8;
        __nv_bfloat16* outp = out + (3 * NG + grp) * DH + vw * 32 + (t & 1) * 16 + (t >> 1) * 8 + g;
        asm volatile("" : "+l"(accp), "+l"(outp), "+r"(off[0]), "+r"(off[1]));

#pragma unroll 1
        for (int j = 0; j < HPC - 1; j++) {
            float acc[2][4];
#pragma unroll
            for (int u = 0; u < 2; u++) { acc[u][0] = acc[u][1] = acc[u][2] = acc[u][3] = 0.f; }
            mbar_wait(bars + (B_W + j) * 8);
            if (vw == 0) TRACE(70 + j);
            uint4 wb[4][2];
#pragma unroll
            for (int sub = 0; sub < 4; sub++) {
                wb[sub][0] = lds128(wofs + (j * 4 + sub) * 256);
                wb[sub][1] = lds128(wofs + (j * 4 + sub) * 256 + 128);
            }
            const uint32_t slot0 = (j & 1) * 4 * STAGE_B;
#pragma unroll
            for (int sub = 0; sub < 4; sub++) {
                const int s = 16 + j * 4 + sub;
                mbar_wait(bars + (B_FULL + s) * 8);
#pragma unroll
                for (int ks = 0; ks < 4; ks++)
#pragma unroll
                    for (int u = 0; u < 2; u++) {
                        const uint4 a = ldsm4t(off[u] + slot0 + sub * STAGE_B + ks * 16 * ROWB);
                        mma(acc[u], a.x, a.y, a.z, a.w, word(wb[sub][ks >> 1], (ks & 1) * 2), word(wb[sub][ks >> 1], (ks & 1) * 2 + 1));
                    }
                if (vw == 0) TRACE(80 + s - 16);
                if (j < 2) {
                    __syncwarp();
                    if (lane == 0) mbar_arrive(bars + (B_FREE + s + NS) * 8);
                }
            }
            const float ox = fsel(acc[0][0] + acc[0][1], acc[1][0] + acc[1][1], t & 1);
            const float oy = fsel(acc[0][2] + acc[0][3], acc[1][2] + acc[1][3], t & 1);
            sts32(sb + OFF_O + (j * DH + vw * 32 + (t & 1) * 16 + (t >> 1) * 8 + g) * 4, __float_as_uint(fsel(ox, oy, t & 2)));
            __syncwarp();
            if (lane == 0) mbar_arrive(bars + (B_O + j) * 8);
        }
        {
            constexpr int KS = 4 / MINI;
            mbar_wait(bars + (B_W + 3) * 8);
            if (vw == 0) TRACE(73);
            uint4 wb[8];
#pragma unroll
            for (int i = 0; i < 8; i++) wb[i] = lds128(wofs + 12 * 256 + i * 128);
            constexpr int NA = V2;
            float acc[NA][2][4];
#pragma unroll
            for (int i = 0; i < 2 * NA; i++) { acc[i >> 1][i & 1][0] = acc[i >> 1][i & 1][1] = acc[i >> 1][i & 1][2] = acc[i >> 1][i & 1][3] = 0.f; }
            uint4 a[16][2];
#pragma unroll
            for (int m = 0; m <= 4 * MINI; m++) {
                auto consume = [&](int mm) {
#pragma unroll
                    for (int x = mm * KS; x < (mm + 1) * KS; x++)
#pragma unroll
                        for (int u = 0; u < 2; u++)
                            mma(acc[x % NA][u], a[x][u].x, a[x][u].y, a[x][u].z, a[x][u].w,
                                word(wb[x >> 1], (x & 1) * 2), word(wb[x >> 1], (x & 1) * 2 + 1));
                };
                if (PIPE == 2 && m == 4 * MINI - 1 && !(OPT & 32)) consume(m - 1);
                if (m < 4 * MINI) {
                    if (OPT & 1) mbar_spin(bars + (B_LAST + m) * 8); else mbar_wait(bars + (B_LAST + m) * 8);
#pragma unroll
                    for (int x = m * KS; x < (m + 1) * KS; x++)
#pragma unroll
                        for (int u = 0; u < 2; u++) if (!(OPT & 32)) a[x][u] = ldsm4t(off[u] + 4 * STAGE_B + x * 16 * ROWB);
                }
                const int mm = PIPE ? m - 1 : m;
                if (mm >= 0 && mm < 4 * MINI && !(OPT & 32) && !(PIPE == 2 && mm == 4 * MINI - 2)) consume(mm);
            }
            if (vw == 0) TRACE(95);
            float r[NA];
#pragma unroll
            for (int i = 0; i < NA; i++)
                r[i] = fsel(fsel(acc[i][0][0] + acc[i][0][1], acc[i][0][2] + acc[i][0][3], t & 2),
                            fsel(acc[i][1][0] + acc[i][1][1], acc[i][1][2] + acc[i][1][3], t & 2), t & 1);
            const float ov = NA == 4 ? (r[0] + r[1 % NA]) + (r[2 % NA] + r[3 % NA]) : NA == 2 ? r[0] + r[1 % NA] : r[0];
            if (OPT & 16) {
                if (c == 5) *outp = __float2bfloat16(ov);
            } else {
                accum2((float2*)accp, ov, outp);
            }
            if (vw < 3) TRACE(108 + vw);
        }
    } else if (warp <= NV + 4) {
        const int w = warp - (NV + 1);
        const uint32_t tile = sb + (w < 3 ? 7 * STAGE_B + w * TILE_B : OFF_X + TILE_B);
        if (elect()) {
#pragma unroll
            for (int m = 0; m < MINI; m++) mbar_init(bars + (B_LAST + w * MINI + m) * 8, 1);
        }
        __syncthreads();
        uint4 fr[16];
        mbar_wait(bars + B_F * 8);
#pragma unroll
        for (int i = 0; i < 16; i++)
            fr[i] = lds128(tile + ((i >> 1) * 8 + 2 * t + (i & 1)) * 128 + ((g ^ (2 * t + (i & 1))) << 4));
        __syncwarp();
        if (lane == 0 && w < 3) mbar_arrive_n(bars + (B_FREE + 7) * 8, NV / 3);
        uint32_t fb[8][8];
#pragma unroll
        for (int i = 0; i < 8; i++)
#pragma unroll
            for (int x = 0; x < 8; x++)
                fb[i][x] = __byte_perm(word(fr[2 * x], i >> 1), word(fr[2 * x + 1], i >> 1), (i & 1) ? 0x7632 : 0x5410);

        if (fb[0][0] != 0x12345) TRACE(144 + w);
        const uint32_t tag = wait_tag(sb);
#pragma unroll 1
        for (int j = 0; j < HPC; j++) {
            if (j == w) {
                mbar_wait(bars + (B_FULL + GATHER_AT + 4 * j) * 8);
                const float2* part = scr->sc + (j * NG + grp) * NC * 32 + lane;
                uint2 pv[NC];
                TRACE(136 + j);
                float2 sc = make_float2(lane, tag);
                if (!(OPT & 64)) {
                    gather_issue<NC, 32>(pv, part);
                    sc = gather_finish<NC, 32>(pv, part, tag);
                }
                if (sc.x != 1234.5f) TRACE(140 + j);
                const float scale = 0.07216878364870322f;
                sc.x *= scale; sc.y *= scale;
                float m = fmaxf(sc.x, sc.y);
#pragma unroll
                for (int o = 16; o > 0; o >>= 1) m = fmaxf(m, __shfl_xor_sync(0xffffffffu, m, o));
                const float e0 = expf(sc.x - m), e1 = expf(sc.y - m);
                float sum = e0 + e1;
#pragma unroll
                for (int o = 16; o > 0; o >>= 1) sum += __shfl_xor_sync(0xffffffffu, sum, o);
                uint32_t hi, lo;
                split2(e0 / sum, e1 / sum, hi, lo);
                sts64(sb + OFF_P + j * 256 + (g >> 1) * 64 + t * 16 + (g & 1) * 8, hi, lo);
                __syncwarp();
                if (lane == 0) mbar_arrive(bars + (B_P + j) * 8);
            }
            mbar_wait(bars + (B_P + j) * 8);
            float d[8][4];
#pragma unroll
            for (int i = 0; i < 8; i++) { d[i][0] = d[i][1] = d[i][2] = d[i][3] = 0.f; }
#pragma unroll
            for (int ks = 0; ks < 4; ks++) {
                const uint4 a = lds128(sb + OFF_P + j * 256 + ks * 64 + t * 16);
#pragma unroll
                for (int i = 0; i < 8; i++) mma(d[i], a.x, a.y, a.z, a.w, fb[i][2 * ks], fb[i][2 * ks + 1]);
            }
            float x[8], y[8];
#pragma unroll
            for (int i = 0; i < 8; i++) { x[i] = d[i][0] + d[i][2]; y[i] = d[i][1] + d[i][3]; }
#pragma unroll
            for (int i = 0; i < 4; i++) { x[i] = fsel(x[i], x[i + 4], g & 4); y[i] = fsel(y[i], y[i + 4], g & 4); }
#pragma unroll
            for (int i = 0; i < 2; i++) { x[i] = fsel(x[i], x[i + 2], g & 2); y[i] = fsel(y[i], y[i + 2], g & 2); }
            uint32_t xh, xl, yh, yl;
            split2(x[0], x[1], xh, xl);
            split2(y[0], y[1], yh, yl);
            sts64(sb + OFF_W + (j * 4 + w) * 256 + (t >> 1) * 128 + (g & 1) * 64 + (g >> 1) * 16 + (t & 1) * 8,
                  (g & 1) ? xl : xh, (g & 1) ? yl : yh);
            __syncwarp();
            if (lane == 0) mbar_arrive(bars + (B_W + j) * 8);
        }
    } else {
        __syncthreads();
        if (lane == 0) {
            const unsigned ep = *(volatile unsigned*)(scr->epoch + blockIdx.x) + 1;
            scr->epoch[blockIdx.x] = ep;
            sts32(sb + OFF_TAG, ep & 1);
            mbar_arrive(bars + B_TAG * 8);
        }
        __syncwarp();
#pragma unroll 1
        for (int j = 0; j < HPC - 1 && !(OPT & 2); j++) {
            mbar_wait(bars + (B_O + j) * 8);
            unsigned char* ap = scr->acc + (grp * 36 + j * 8 + (lane >> 3)) * ACC_PITCH + (lane & 7) * 16;
            __nv_bfloat16* op = out + (j * NG + grp) * DH + lane;
            float o[2][3];
            float4 r[2];
#pragma unroll
            for (int i = 0; i < 2; i++) {
#pragma unroll
                for (int x = 0; x < 3; x++) o[i][x] = __uint_as_float(lds32(sb + OFF_O + (j * DH + (i * 3 + x) * 32 + lane) * 4));
                r[i] = accum4_issue(ap + i * 4 * ACC_PITCH, o[i][0], o[i][1], o[i][2]);
            }
#pragma unroll
            for (int i = 0; i < 2; i++)
                if (r[i].w == (float)(NC - 1)) {
                    op[i * 96] = __float2bfloat16(r[i].x + o[i][0]);
                    op[i * 96 + 32] = __float2bfloat16(r[i].y + o[i][1]);
                    op[i * 96 + 64] = __float2bfloat16(r[i].z + o[i][2]);
                    *(float4*)(ap + i * 4 * ACC_PITCH) = make_float4(0.f, 0.f, 0.f, 0.f);
                }
            TRACE(154 + j * 3);
        }
    }
}

inline CUtensorMap make_map(const void* p, uint64_t inner, uint64_t rows, uint32_t box_rows) {
    typedef CUresult (*EncodeFn)(CUtensorMap*, CUtensorMapDataType, cuuint32_t, void*, const cuuint64_t*, const cuuint64_t*,
                                 const cuuint32_t*, const cuuint32_t*, CUtensorMapInterleave, CUtensorMapSwizzle,
                                 CUtensorMapL2promotion, CUtensorMapFloatOOBfill);
    void* fn = nullptr;
    cudaDriverEntryPointQueryResult qr;
    cudaGetDriverEntryPoint("cuTensorMapEncodeTiled", &fn, cudaEnableDefault, &qr);
    CUtensorMap m;
    const cuuint64_t dims[2] = {inner, rows};
    const cuuint64_t strides[1] = {inner * 2};
    const cuuint32_t box[2] = {64, box_rows};
    const cuuint32_t estr[2] = {1, 1};
    ((EncodeFn)fn)(&m, CU_TENSOR_MAP_DATA_TYPE_BFLOAT16, 2, (void*)p, dims, strides, box, estr, CU_TENSOR_MAP_INTERLEAVE_NONE,
                   CU_TENSOR_MAP_SWIZZLE_128B, CU_TENSOR_MAP_L2_PROMOTION_NONE, CU_TENSOR_MAP_FLOAT_OOB_FILL_NONE);
    return m;
}

template <class Kern>
inline void launch(Kern kern, int mini, int smem_bytes, const void* q, const void* k, const void* v, const void* e, const void* f, void* out) {
    void* scr = nullptr;
    cudaGetSymbolAddress(&scr, g_scratch);
    cudaFuncSetAttribute(kern, cudaFuncAttributeMaxDynamicSharedMemorySize, smem_bytes);
    kern<<<NCTA, NTHREADS, smem_bytes>>>((const __nv_bfloat16*)k, (const __nv_bfloat16*)q, (__nv_bfloat16*)out, (Scratch*)scr,
                                         make_map(v, 64, (uint64_t)H * SKV * 3, 192), make_map(e, SKV, 64, 64),
                                         make_map(f, SKV, 64, 64), make_map(v, 64, (uint64_t)H * SKV * 3, 192 / mini));
}

}

extern "C" void kernel_launch(void* const* d_in, const int* in_sizes, int n_in, void* d_out, int out_size) {
    lf::launch(lf::linformer_decode_kernel<3, 9, 1, 2, 1, 2, 2, 4, 3, 32>, 1, lf::SMEM_BYTES, d_in[0], d_in[1], d_in[2], d_in[3], d_in[4], d_out);
}
```

```cpp
#include <cuda.h>
#include <cuda_runtime.h>
#include <cuda_bf16.h>
#include <stdint.h>

namespace lf {

constexpr int H = 32, SKV = 4096, DH = 192;
constexpr int NCTA = 128;
constexpr int NC = 16;
constexpr int NG = 8;
constexpr int HPC = 4;
constexpr int ROWB = DH * 2;
constexpr int STAGE_B = 64 * ROWB;
constexpr int NS = 8;
constexpr int NSTAGE = 32;
constexpr int NV = 6;
constexpr int NTHREADS = (1 + NV + 4 + 1) * 32;

constexpr int TILE_B = 64 * 128;
constexpr int OFF_X = NS * STAGE_B;
constexpr int OFF_W = OFF_X + 2 * TILE_B;
constexpr int OFF_P = OFF_W + 4096;
constexpr int OFF_S = OFF_P + 1024;
constexpr int OFF_Q = OFF_S + 4096;
constexpr int OFF_O = OFF_Q + 1536;
constexpr int OFF_BAR = OFF_O + 2304;
constexpr int B_FULL = 0, B_FREE = 32 - 6, B_S = 58, B_P = 62, B_W = 66, B_O = 70, B_E = 73, B_F = 74, NBAR = 75;
constexpr int SMEM_BYTES = OFF_BAR + NBAR * 8;

constexpr int SPIN_LIMIT = 1 << 22;

constexpr int PITCH = 4224;
constexpr int L_SC = 0, L_O = 16, L_LAST = 40, L_GROUP = 52;
__device__ __align__(128) unsigned char g_acc[NG * L_GROUP * PITCH];

#define TRACE(id)

__device__ __forceinline__ uint32_t smem_u32(const void* p) { return (uint32_t)__cvta_generic_to_shared(p); }
__device__ __forceinline__ void mbar_init(uint32_t bar, uint32_t cnt) {
    asm volatile("mbarrier.init.shared::cta.b64 [%0], %1;" :: "r"(bar), "r"(cnt) : "memory");
}
__device__ __forceinline__ void mbar_arm(uint32_t bar, uint32_t bytes) {
    mbar_init(bar, 1);
    asm volatile("mbarrier.arrive.expect_tx.shared::cta.b64 _, [%0], %1;" :: "r"(bar), "r"(bytes) : "memory");
}
__device__ __forceinline__ void mbar_arrive(uint32_t bar) {
    asm volatile("mbarrier.arrive.shared::cta.b64 _, [%0];" :: "r"(bar) : "memory");
}
__device__ __forceinline__ void mbar_arrive_n(uint32_t bar, uint32_t n) {
    asm volatile("mbarrier.arrive.shared::cta.b64 _, [%0], %1;" :: "r"(bar), "r"(n) : "memory");
}
__device__ __forceinline__ void mbar_wait(uint32_t bar) {
    asm volatile("{\n.reg .pred p;\n.reg .u32 n;\nmov.u32 n, 0;\n"
                 "LF_WAIT_%=:\n"
                 "mbarrier.try_wait.parity.shared::cta.b64 p, [%0], 0;\n"
                 "@p bra LF_DONE_%=;\n"
                 "add.u32 n, n, 1;\n"
                 "setp.lt.u32 p, n, %1;\n"
                 "@p bra LF_WAIT_%=;\n"
                 "trap;\n"
                 "LF_DONE_%=:\n}"
                 :: "r"(bar), "n"(SPIN_LIMIT) : "memory");
}
constexpr uint64_t EVICT_FIRST = 0x12F0000000000000ull;
__device__ __forceinline__ void bulk_g2s(uint32_t dst, const void* src, uint32_t bytes, uint32_t bar) {
    asm volatile("cp.async.bulk.shared::cluster.global.mbarrier::complete_tx::bytes.L2::cache_hint [%0], [%1], %2, [%3], %4;"
                 :: "r"(dst), "l"(src), "r"(bytes), "r"(bar), "l"(EVICT_FIRST) : "memory");
}
__device__ __forceinline__ void tile_g2s(uint32_t dst, const CUtensorMap* map, int n0, uint32_t bar) {
    asm volatile("cp.async.bulk.tensor.2d.shared::cluster.global.mbarrier::complete_tx::bytes [%0], [%1, {%2, %3}], [%4];"
                 :: "r"(dst), "l"(map), "r"(n0), "r"(0), "r"(bar) : "memory");
}
__device__ __forceinline__ void lines_g2s(uint32_t dst, const CUtensorMap* map, int line0, uint32_t bar) {
    asm volatile("cp.async.bulk.tensor.2d.shared::cluster.global.mbarrier::complete_tx::bytes.L2::cache_hint [%0], [%1, {%2, %3}], [%4], %5;"
                 :: "r"(dst), "l"(map), "r"(0), "r"(line0), "r"(bar), "l"(EVICT_FIRST) : "memory");
}
__device__ __forceinline__ bool elect() {
    uint32_t p;
    asm volatile("{\n.reg .pred P;\nelect.sync _|P, 0xffffffff;\nselp.u32 %0, 1, 0, P;\n}" : "=r"(p));
    return p;
}
__device__ __forceinline__ void mma(float (&d)[4], uint32_t a0, uint32_t a1, uint32_t a2, uint32_t a3, uint32_t b0, uint32_t b1) {
    asm volatile("mma.sync.aligned.m16n8k16.row.col.f32.bf16.bf16.f32 {%0,%1,%2,%3}, {%4,%5,%6,%7}, {%8,%9}, {%0,%1,%2,%3};"
                 : "+f"(d[0]), "+f"(d[1]), "+f"(d[2]), "+f"(d[3])
                 : "r"(a0), "r"(a1), "r"(a2), "r"(a3), "r"(b0), "r"(b1));
}
__device__ __forceinline__ uint4 lds128(uint32_t addr) {
    uint4 v;
    asm volatile("ld.shared.v4.u32 {%0,%1,%2,%3}, [%4];" : "=r"(v.x), "=r"(v.y), "=r"(v.z), "=r"(v.w) : "r"(addr) : "memory");
    return v;
}
__device__ __forceinline__ float2 lds64f(uint32_t addr) {
    float2 v;
    asm volatile("ld.shared.v2.f32 {%0,%1}, [%2];" : "=f"(v.x), "=f"(v.y) : "r"(addr) : "memory");
    return v;
}
__device__ __forceinline__ uint32_t lds32(uint32_t addr) {
    uint32_t v;
    asm volatile("ld.shared.u32 %0, [%1];" : "=r"(v) : "r"(addr) : "memory");
    return v;
}
__device__ __forceinline__ void sts64(uint32_t addr, uint32_t x, uint32_t y) {
    asm volatile("st.shared.v2.u32 [%0], {%1,%2};" :: "r"(addr), "r"(x), "r"(y) : "memory");
}
__device__ __forceinline__ void sts32(uint32_t addr, float x) {
    asm volatile("st.shared.f32 [%0], %1;" :: "r"(addr), "f"(x) : "memory");
}
__device__ __forceinline__ uint4 ldsm4t(uint32_t addr) {
    uint4 v;
    asm volatile("ldmatrix.sync.aligned.m8n8.x4.trans.shared.b16 {%0,%1,%2,%3}, [%4];"
                 : "=r"(v.x), "=r"(v.y), "=r"(v.z), "=r"(v.w) : "r"(addr) : "memory");
    return v;
}
__device__ __forceinline__ float fsel(float a, float b, uint32_t pick_b) {
    float r;
    asm("{\n.reg .pred s;\nsetp.ne.u32 s, %3, 0;\nselp.f32 %0, %2, %1, s;\n}" : "=f"(r) : "f"(a), "f"(b), "r"(pick_b));
    return r;
}
__device__ __forceinline__ uint32_t pack_hi(float x, float y) {
    uint32_t r;
    asm("cvt.rn.bf16x2.f32 %0, %1, %2;" : "=r"(r) : "f"(y), "f"(x));
    return r;
}
__device__ __forceinline__ void split2(float x, float y, uint32_t& hi, uint32_t& lo) {
    hi = pack_hi(x, y);
    lo = pack_hi(x - __uint_as_float(hi << 16), y - __uint_as_float(hi & 0xffff0000u));
}
__device__ __forceinline__ uint32_t word(const uint4& v, int i) { return i == 0 ? v.x : i == 1 ? v.y : i == 2 ? v.z : v.w; }

__device__ __forceinline__ float4 atom_add4(void* p, float x, float y, float z, float w) {
    float4 r;
    asm volatile("atom.relaxed.gpu.global.add.v4.f32 {%0,%1,%2,%3}, [%4], {%5,%6,%7,%8};"
                 : "=f"(r.x), "=f"(r.y), "=f"(r.z), "=f"(r.w) : "l"(p), "f"(x), "f"(y), "f"(z), "f"(w) : "memory");
    return r;
}
__device__ __forceinline__ void red_add4(void* p, float x, float y, float z, float w) {
    asm volatile("red.relaxed.gpu.global.add.v4.f32 [%0], {%1,%2,%3,%4};" :: "l"(p), "f"(x), "f"(y), "f"(z), "f"(w) : "memory");
}
__device__ __forceinline__ void clear16(void* p) {
    asm volatile("st.global.v4.u32 [%0], {%1,%1,%1,%1};" :: "l"(p), "r"(0) : "memory");
}
__device__ __forceinline__ float column_value(const float (&a)[2][4], int t) {
    return fsel(fsel(a[0][0] + a[0][1], a[0][2] + a[0][3], t & 2), fsel(a[1][0] + a[1][1], a[1][2] + a[1][3], t & 2), t & 1);
}

template <int DEPTH, int GATHER_AT, int F_AT, int OPT, int D2, int SW, int GAP = 0, int GAP_END = 32, int PF = 8192>
__global__ void __launch_bounds__(NTHREADS, 1)
linformer_decode_kernel(const __nv_bfloat16* __restrict__ k, const __nv_bfloat16* __restrict__ q,
                        __nv_bfloat16* __restrict__ out, unsigned char* __restrict__ acc_all,
                        const __grid_constant__ CUtensorMap vmap, const __grid_constant__ CUtensorMap emap,
                        const __grid_constant__ CUtensorMap fmap) {
    extern __shared__ __align__(1024) unsigned char smem[];
    const uint32_t sb = smem_u32(smem);
    const uint32_t bars = sb + OFF_BAR;
    const int grp = blockIdx.x & (NG - 1), c = blockIdx.x >> 3;

    if (OPT & 2) {
        const uint32_t ofs = (grp * SKV + c * 256) * ROWB + ((OPT & 4) ? STAGE_B : 0) + (threadIdx.x >> 5) * PF;
        if (elect()) asm volatile("cp.async.bulk.prefetch.L2.global [%0], %1;" :: "l"((const char*)k + ofs), "r"(PF) : "memory");
    }
    if (OPT & 8) {
        const uint32_t ofs = (grp * SKV + c * 256) * ROWB + (threadIdx.x >> 1) * 128;
        if (!(threadIdx.x & 1)) asm volatile("prefetch.global.L2 [%0];" :: "l"((const char*)k + ofs) : "memory");
    }
    if (OPT & 16) {
        const uint32_t ofs = (grp * SKV + c * 256) * ROWB + threadIdx.x * 128;
        asm volatile("prefetch.global.L2 [%0];" :: "l"((const char*)k + ofs) : "memory");
    }
    if (threadIdx.x < 32) {
        const bool leader = elect();
        const int row0 = grp * SKV + c * 256;
        auto issue_k = [&](int s) {
            const int row = row0 + (s >> 2) * NG * SKV + (s & 3) * 64;
            bulk_g2s(sb + (s & (NS - 1)) * STAGE_B, (const char*)k + (size_t)row * ROWB, STAGE_B, bars + (B_FULL + s) * 8);
        };
        auto issue_v = [&](int s) {
            const int row = row0 + ((s >> 2) & 3) * NG * SKV + (s & 3) * 64;
            lines_g2s(sb + (s & (NS - 1)) * STAGE_B, &vmap, row * 3, bars + (B_FULL + s) * 8);
        };
        if (leader) {
            if (PF && !(OPT & 2)) asm volatile("cp.async.bulk.prefetch.L2.global [%0], %1;" :: "l"((const char*)k + (size_t)row0 * ROWB), "r"(PF) : "memory");
            mbar_arm(bars + B_FULL * 8, STAGE_B);
            issue_k(0);
        }
        __syncthreads();
        if (leader) {
#pragma unroll
            for (int j = 0; j < HPC; j++) bulk_g2s(sb + OFF_Q + j * ROWB, q + (j * NG + grp) * DH, ROWB, bars + B_E * 8);
#pragma unroll
            for (int w = 0; w < 4; w++)
                tile_g2s(sb + (w < 3 ? 6 * STAGE_B + w * TILE_B : OFF_X), &emap, c * 256 + w * 64, bars + B_E * 8);
#pragma unroll
            for (int s = 1; s <= DEPTH; s++) {
                if (s == F_AT) {
#pragma unroll
                    for (int w = 0; w < 4; w++)
                        tile_g2s(sb + (w < 3 ? 7 * STAGE_B + w * TILE_B : OFF_X + TILE_B), &fmap, c * 256 + w * 64, bars + B_F * 8);
                }
                if (s < DEPTH) issue_k(s);
            }
            uint32_t next_ok = (uint32_t)clock();
#pragma unroll 1
            for (int s = DEPTH; s < NSTAGE; s++) {
                if (s >= 6) mbar_wait(bars + (B_FREE + s) * 8);
                mbar_wait(bars + (B_FULL + s - (s < SW ? DEPTH : D2)) * 8);
                if (GAP && s < GAP_END) {
                    uint32_t now;
                    do { now = (uint32_t)clock(); } while ((int)(now - next_ok) < 0);
                    next_ok = now + GAP;
                }
                TRACE(1 + s - DEPTH);
                if (s < 16) issue_k(s); else issue_v(s);
            }
        }
        return;
    }

    const int warp = __shfl_sync(0xffffffffu, threadIdx.x >> 5, 0), lane = threadIdx.x & 31;
    const int g = lane >> 2, t = lane & 3;
    unsigned char* const acc_g = acc_all + grp * L_GROUP * PITCH;
    const int entry16 = (lane >> 3) * PITCH + (lane & 7) * 16;

    if (warp <= NV) {
        const int vw = warp - 1;
        if (elect()) {
#pragma unroll
            for (int i = 0; i < 5; i++) {
                const int s = vw * 5 + i;
                mbar_arm(bars + (B_FULL + 1 + s) * 8, STAGE_B);
                if (s < 26) mbar_init(bars + (B_FREE + 6 + s) * 8, NV);
            }
        }
        __syncthreads();

        if (vw < 4) {
            const int w = vw;
            const uint32_t tile = sb + (w < 3 ? 6 * STAGE_B + w * TILE_B : OFF_X);
            uint32_t ef[4][4][4];
            mbar_wait(bars + B_E * 8);
#pragma unroll
            for (int i = 0; i < 8; i++) {
                const uint4 ea = lds128(tile + (i * 8 + g) * 128 + (((2 * t) ^ g) << 4));
                const uint4 eb = lds128(tile + (i * 8 + g) * 128 + (((2 * t + 1) ^ g) << 4));
#pragma unroll
                for (int ks = 0; ks < 4; ks++) { ef[i >> 1][ks][i & 1] = word(ea, ks); ef[i >> 1][ks][2 + (i & 1)] = word(eb, ks); }
            }
            __syncwarp();
            if (lane == 0 && w < 3) mbar_arrive_n(bars + (B_FREE + 6) * 8, NV / 3);

            const uint32_t krow = sb + ((g & 3) * 16 + (g >> 2) * 8) * ROWB + t * 16;
            const uint32_t kofs0 = krow + (g & 1) * 64, kofs1 = krow + ((g & 1) ^ 1) * 64;
            const uint32_t qofs0 = sb + OFF_Q + t * 16 + (g & 1) * 4 + (g & 2) * 32, qofs1 = qofs0 ^ 64;
            const uint32_t m0 = (g == t) ? 0xffffffffu : 0u, m1 = (g == t + 4) ? 0xffffffffu : 0u;
#pragma unroll 1
            for (int j = 0; j < HPC; j++) {
                const int s = j * 4 + w;
                uint32_t qf[6][2];
#pragma unroll
                for (int i = 0; i < 6; i++) {
                    qf[i][0] = lds32(((i & 1) ? qofs1 : qofs0) + j * ROWB + (i >> 1) * 128);
                    qf[i][1] = lds32(((i & 1) ? qofs1 : qofs0) + j * ROWB + (i >> 1) * 128 + 8);
                }
                const uint32_t slot = (s & (NS - 1)) * STAGE_B;
                mbar_wait(bars + (B_FULL + s) * 8);
                float d[8][4];
#pragma unroll
                for (int u = 0; u < 8; u++) { d[u][0] = d[u][1] = d[u][2] = d[u][3] = 0.f; }
#pragma unroll
                for (int i = 0; i < 6; i++)
#pragma unroll
                    for (int u = 0; u < 8; u++) {
                        const uint4 kv = lds128(((i & 1) ? kofs1 : kofs0) + slot + u * ROWB + (i >> 1) * 128);
                        mma(d[u], kv.x, kv.y, kv.z, kv.w, qf[i][0], qf[i][1]);
                    }
                __syncwarp();
                if (lane == 0) mbar_arrive_n(bars + (B_FREE + s + NS) * 8, NV);

                float d2[4][4];
#pragma unroll
                for (int i = 0; i < 4; i++) { d2[i][0] = d2[i][1] = d2[i][2] = d2[i][3] = 0.f; }
#pragma unroll
                for (int ks = 0; ks < 4; ks++) {
                    uint32_t hi, lo;
                    split2(d[2 * ks][0] + d[2 * ks][3], d[2 * ks + 1][0] + d[2 * ks + 1][3], hi, lo);
#pragma unroll
                    for (int i = 0; i < 4; i++) mma(d2[i], ef[i][ks][0], ef[i][ks][1], ef[i][ks][2], ef[i][ks][3], hi & m0, hi & m1);
#pragma unroll
                    for (int i = 0; i < 4; i++) mma(d2[i], ef[i][ks][0], ef[i][ks][1], ef[i][ks][2], ef[i][ks][3], lo & m0, lo & m1);
                }
                float x[4], y[4];
#pragma unroll
                for (int i = 0; i < 4; i++) { x[i] = d2[i][0] + d2[i][1]; y[i] = d2[i][2] + d2[i][3]; }
#pragma unroll
                for (int i = 0; i < 2; i++) {
                    x[i] = fsel(x[i], x[i + 2], t & 2) + __shfl_xor_sync(0xffffffffu, fsel(x[i + 2], x[i], t & 2), 2);
                    y[i] = fsel(y[i], y[i + 2], t & 2) + __shfl_xor_sync(0xffffffffu, fsel(y[i + 2], y[i], t & 2), 2);
                }
                const float sx = fsel(x[0], x[1], t & 1) + __shfl_xor_sync(0xffffffffu, fsel(x[1], x[0], t & 1), 1);
                const float sy = fsel(y[0], y[1], t & 1) + __shfl_xor_sync(0xffffffffu, fsel(y[1], y[0], t & 1), 1);
                sts32(sb + OFF_S + (j * 4 + w) * 256 + (16 * t + g) * 4, sx);
                sts32(sb + OFF_S + (j * 4 + w) * 256 + (16 * t + 8 + g) * 4, sy);
                __syncwarp();
                if (lane == 0) mbar_arrive(bars + (B_S + j) * 8);
            }
        }

        const int mat = lane >> 3, mi = lane & 7;
        uint32_t off[2];
#pragma unroll
        for (int u = 0; u < 2; u++) {
            const int cc = vw * 4 + u * 2 + (mat & 1), blk = cc >> 3;
            off[u] = sb + ((mat >> 1) * 8 + mi) * ROWB + blk * 128 + (((cc & 7) ^ ((3 * mi + blk) & 7)) << 4);
        }
        const uint32_t wofs = sb + OFF_W + (g & 1) * 64 + t * 16;
        const int col = vw * 32 + (t & 1) * 16 + (t >> 1) * 8 + g;
        unsigned char* accp = acc_g + (L_LAST + vw * 2 + (lane >> 4)) * PITCH + (lane & 15) * 8;
        unsigned char* scp = acc_g + (L_SC + 12) * PITCH + entry16;
        __nv_bfloat16* outp = out + (3 * NG + grp) * DH + col;
        asm volatile("" : "+l"(accp), "+l"(scp), "+l"(outp), "+r"(off[0]), "+r"(off[1]));

#pragma unroll 1
        for (int j = 0; j < HPC - 1; j++) {
            float acc[2][4];
#pragma unroll
            for (int u = 0; u < 2; u++) { acc[u][0] = acc[u][1] = acc[u][2] = acc[u][3] = 0.f; }
            mbar_wait(bars + (B_W + j) * 8);
            if (vw == 0) TRACE(70 + j);
            uint4 wb[8];
#pragma unroll
            for (int i = 0; i < 8; i++) wb[i] = lds128(wofs + j * 1024 + i * 128);
            const uint32_t slot0 = (j & 1) * 4 * STAGE_B;
#pragma unroll
            for (int sub = 0; sub < 4; sub++) {
                const int s = 16 + j * 4 + sub;
                mbar_wait(bars + (B_FULL + s) * 8);
#pragma unroll
                for (int x = sub * 4; x < sub * 4 + 4; x++)
#pragma unroll
                    for (int u = 0; u < 2; u++) {
                        const uint4 a = ldsm4t(off[u] + slot0 + x * 16 * ROWB);
                        mma(acc[u], a.x, a.y, a.z, a.w, word(wb[x >> 1], (x & 1) * 2), word(wb[x >> 1], (x & 1) * 2 + 1));
                    }
                if (j < 2) {
                    __syncwarp();
                    if (lane == 0) mbar_arrive(bars + (B_FREE + s + NS) * 8);
                }
            }
            sts32(sb + OFF_O + (j * DH + col) * 4, column_value(acc, t));
            __syncwarp();
            if (lane == 0) mbar_arrive(bars + (B_O + j) * 8);
        }

        mbar_wait(bars + (B_W + 3) * 8);
        if (vw == 0) TRACE(73);
        uint4 wb[8];
#pragma unroll
        for (int i = 0; i < 8; i++) wb[i] = lds128(wofs + 3 * 1024 + i * 128);
        float acc[2][2][4];
#pragma unroll
        for (int i = 0; i < 4; i++) { acc[i >> 1][i & 1][0] = acc[i >> 1][i & 1][1] = acc[i >> 1][i & 1][2] = acc[i >> 1][i & 1][3] = 0.f; }
        uint4 a[16][2];
        auto load = [&](int sub) {
            mbar_wait(bars + (B_FULL + 28 + sub) * 8);
#pragma unroll
            for (int x = sub * 4; x < sub * 4 + 4; x++)
#pragma unroll
                for (int u = 0; u < 2; u++) if (!(OPT & 32)) a[x][u] = ldsm4t(off[u] + 4 * STAGE_B + x * 16 * ROWB);
        };
        auto consume = [&](int sub) {
#pragma unroll
            for (int x = sub * 4; x < sub * 4 + 4; x++)
#pragma unroll
                for (int u = 0; u < 2; u++)
                    if (!(OPT & 32)) mma(acc[x & 1][u], a[x][u].x, a[x][u].y, a[x][u].z, a[x][u].w,
                        word(wb[x >> 1], (x & 1) * 2), word(wb[x >> 1], (x & 1) * 2 + 1));
        };
        load(0);
        load(1); consume(0);
        load(2); consume(1); consume(2);
        load(3); consume(3);
        if (vw == 0) TRACE(95);
        const float ov = column_value(acc[0], t) + column_value(acc[1], t);
        asm volatile("{\n.reg .pred p, z;\n.reg .f32 a, n;\n.reg .b16 h;\n"
                     "atom.relaxed.gpu.global.add.v2.f32 {a, n}, [%0], {%3, 0f3F800000};\n"
                     "setp.eq.f32 p, n, 0f41700000;\n"
                     "add.f32 a, a, %3;\n"
                     "cvt.rn.bf16.f32 h, a;\n"
                     "@p st.global.b16 [%1], h;\n"
                     "@p st.global.v2.u32 [%0], {0, 0};\n"
                     "setp.eq.and.u32 z, %4, 0, p;\n"
                     "@z st.global.v4.u32 [%2], {0, 0, 0, 0};\n}"
                     :: "l"(accp), "l"(outp), "l"(scp), "f"(ov), "r"(vw) : "memory");
        if (vw < 3) TRACE(108 + vw);
    } else if (warp <= NV + 4) {
        const int w = warp - (NV + 1);
        const uint32_t tile = sb + (w < 3 ? 7 * STAGE_B + w * TILE_B : OFF_X + TILE_B);
        if (elect()) {
            mbar_init(bars + (B_S + w) * 8, 4);
            mbar_init(bars + (B_P + w) * 8, 1);
            mbar_init(bars + (B_W + w) * 8, 4);
        }
        __syncthreads();
        uint4 fr[16];
        mbar_wait(bars + B_F * 8);
#pragma unroll
        for (int i = 0; i < 16; i++)
            fr[i] = lds128(tile + ((i >> 1) * 8 + 2 * t + (i & 1)) * 128 + ((g ^ (2 * t + (i & 1))) << 4));
        __syncwarp();
        if (lane == 0 && w < 3) mbar_arrive_n(bars + (B_FREE + 7) * 8, NV / 3);
        uint32_t fb[8][8];
#pragma unroll
        for (int i = 0; i < 8; i++)
#pragma unroll
            for (int x = 0; x < 8; x++)
                fb[i][x] = __byte_perm(word(fr[2 * x], i >> 1), word(fr[2 * x + 1], i >> 1), (i & 1) ? 0x7632 : 0x5410);

#pragma unroll 1
        for (int j = 0; j < HPC; j++) {
            if (j == w) {
                mbar_wait(bars + (B_FULL + GATHER_AT + 4 * j) * 8);
                TRACE(136 + j);
                float4 sc;
#pragma unroll 1
                for (int it = 0;; it++) {
                    sc = atom_add4(acc_g + (L_SC + 4 * j) * PITCH + entry16, 0.f, 0.f, 0.f, 0.f);
                    if (__all_sync(0xffffffffu, sc.z == (float)NC)) break;
                    if (it > SPIN_LIMIT) __trap();
                    __nanosleep(OPT & 1 ? 500 : 100);
                }
                TRACE(140 + j);
                const float scale = 0.07216878364870322f;
                sc.x *= scale; sc.y *= scale;
                float m = fmaxf(sc.x, sc.y);
#pragma unroll
                for (int o = 16; o > 0; o >>= 1) m = fmaxf(m, __shfl_xor_sync(0xffffffffu, m, o));
                const float e0 = expf(sc.x - m), e1 = expf(sc.y - m);
                float sum = e0 + e1;
#pragma unroll
                for (int o = 16; o > 0; o >>= 1) sum += __shfl_xor_sync(0xffffffffu, sum, o);
                uint32_t hi, lo;
                split2(e0 / sum, e1 / sum, hi, lo);
                sts64(sb + OFF_P + j * 256 + (g >> 1) * 64 + t * 16 + (g & 1) * 8, hi, lo);
                __syncwarp();
                if (lane == 0) mbar_arrive(bars + (B_P + j) * 8);
            }
            mbar_wait(bars + (B_P + j) * 8);
            float d[8][4];
#pragma unroll
            for (int i = 0; i < 8; i++) { d[i][0] = d[i][1] = d[i][2] = d[i][3] = 0.f; }
#pragma unroll
            for (int ks = 0; ks < 4; ks++) {
                const uint4 a = lds128(sb + OFF_P + j * 256 + ks * 64 + t * 16);
#pragma unroll
                for (int i = 0; i < 8; i++) mma(d[i], a.x, a.y, a.z, a.w, fb[i][2 * ks], fb[i][2 * ks + 1]);
            }
            float x[8], y[8];
#pragma unroll
            for (int i = 0; i < 8; i++) { x[i] = d[i][0] + d[i][2]; y[i] = d[i][1] + d[i][3]; }
#pragma unroll
            for (int i = 0; i < 4; i++) { x[i] = fsel(x[i], x[i + 4], g & 4); y[i] = fsel(y[i], y[i + 4], g & 4); }
#pragma unroll
            for (int i = 0; i < 2; i++) { x[i] = fsel(x[i], x[i + 2], g & 2); y[i] = fsel(y[i], y[i + 2], g & 2); }
            uint32_t xh, xl, yh, yl;
            split2(x[0], x[1], xh, xl);
            split2(y[0], y[1], yh, yl);
            sts64(sb + OFF_W + (j * 4 + w) * 256 + (t >> 1) * 128 + (g & 1) * 64 + (g >> 1) * 16 + (t & 1) * 8,
                  (g & 1) ? xl : xh, (g & 1) ? yl : yh);
            __syncwarp();
            if (lane == 0) mbar_arrive(bars + (B_W + j) * 8);
        }
    } else {
        if (elect()) {
            asm volatile("prefetch.tensormap [%0];" :: "l"(&emap) : "memory");
            asm volatile("prefetch.tensormap [%0];" :: "l"(&fmap) : "memory");
            asm volatile("prefetch.tensormap [%0];" :: "l"(&vmap) : "memory");
            mbar_arm(bars + B_E * 8, 4 * TILE_B + HPC * ROWB);
            mbar_arm(bars + B_F * 8, 4 * TILE_B);
            mbar_arm(bars + (B_FULL + 31) * 8, STAGE_B);
#pragma unroll
            for (int j = 0; j < 3; j++) mbar_init(bars + (B_O + j) * 8, NV);
        }
        __syncthreads();
#pragma unroll 1
        for (int j = 0; j < HPC; j++) {
            mbar_wait(bars + (B_S + j) * 8);
            const float2 p0 = lds64f(sb + OFF_S + (j * 4 + 0) * 256 + lane * 8);
            const float2 p1 = lds64f(sb + OFF_S + (j * 4 + 1) * 256 + lane * 8);
            const float2 p2 = lds64f(sb + OFF_S + (j * 4 + 2) * 256 + lane * 8);
            const float2 p3 = lds64f(sb + OFF_S + (j * 4 + 3) * 256 + lane * 8);
            red_add4(acc_g + (L_SC + 4 * j) * PITCH + entry16, (p0.x + p1.x) + (p2.x + p3.x), (p0.y + p1.y) + (p2.y + p3.y), 1.f, 0.f);
            TRACE(130 + j);
        }
#pragma unroll 1
        for (int j = 0; j < HPC - 1; j++) {
            mbar_wait(bars + (B_O + j) * 8);
            unsigned char* ap = acc_g + (L_O + 8 * j) * PITCH + entry16;
            __nv_bfloat16* op = out + (j * NG + grp) * DH + lane;
            float o[2][3];
            float4 r[2];
#pragma unroll
            for (int i = 0; i < 2; i++) {
#pragma unroll
                for (int x = 0; x < 3; x++) o[i][x] = __uint_as_float(lds32(sb + OFF_O + (j * DH + (i * 3 + x) * 32 + lane) * 4));
                r[i] = atom_add4(ap + i * 4 * PITCH, o[i][0], o[i][1], o[i][2], 1.f);
            }
#pragma unroll
            for (int i = 0; i < 2; i++)
                if (r[i].w == (float)(NC - 1)) {
                    op[i * 96] = __float2bfloat16(r[i].x + o[i][0]);
                    op[i * 96 + 32] = __float2bfloat16(r[i].y + o[i][1]);
                    op[i * 96 + 64] = __float2bfloat16(r[i].z + o[i][2]);
                    clear16(ap + i * 4 * PITCH);
                    if (i == 0) clear16(acc_g + (L_SC + 4 * j) * PITCH + entry16);
                }
            TRACE(154 + j * 3);
        }
    }
}

inline CUtensorMap make_map(const void* p, uint64_t inner, uint64_t rows, uint32_t box_rows) {
    typedef CUresult (*EncodeFn)(CUtensorMap*, CUtensorMapDataType, cuuint32_t, void*, const cuuint64_t*, const cuuint64_t*,
                                 const cuuint32_t*, const cuuint32_t*, CUtensorMapInterleave, CUtensorMapSwizzle,
                                 CUtensorMapL2promotion, CUtensorMapFloatOOBfill);
    void* fn = nullptr;
    cudaDriverEntryPointQueryResult qr;
    cudaGetDriverEntryPoint("cuTensorMapEncodeTiled", &fn, cudaEnableDefault, &qr);
    CUtensorMap m;
    const cuuint64_t dims[2] = {inner, rows};
    const cuuint64_t strides[1] = {inner * 2};
    const cuuint32_t box[2] = {64, box_rows};
    const cuuint32_t estr[2] = {1, 1};
    ((EncodeFn)fn)(&m, CU_TENSOR_MAP_DATA_TYPE_BFLOAT16, 2, (void*)p, dims, strides, box, estr, CU_TENSOR_MAP_INTERLEAVE_NONE,
                   CU_TENSOR_MAP_SWIZZLE_128B, CU_TENSOR_MAP_L2_PROMOTION_NONE, CU_TENSOR_MAP_FLOAT_OOB_FILL_NONE);
    return m;
}

template <class Kern>
inline void launch(Kern kern, int smem_bytes, const void* q, const void* k, const void* v, const void* e, const void* f, void* out) {
    void* acc = nullptr;
    cudaGetSymbolAddress(&acc, g_acc);
    cudaFuncSetAttribute(kern, cudaFuncAttributeMaxDynamicSharedMemorySize, smem_bytes);
    kern<<<NCTA, NTHREADS, smem_bytes>>>((const __nv_bfloat16*)k, (const __nv_bfloat16*)q, (__nv_bfloat16*)out, (unsigned char*)acc,
                                         make_map(v, 64, (uint64_t)H * SKV * 3, 192), make_map(e, SKV, 64, 64),
                                         make_map(f, SKV, 64, 64));
}

}

extern "C" void kernel_launch(void* const* d_in, const int* in_sizes, int n_in, void* d_out, int out_size) {
    lf::launch(lf::linformer_decode_kernel<4, 10, 2, 0, 3, 29>, lf::SMEM_BYTES, d_in[0], d_in[1], d_in[2], d_in[3], d_in[4], d_out);
}
```

```cpp
#include <cuda.h>
#include <cuda_runtime.h>
#include <cuda_bf16.h>
#include <stdint.h>

namespace lf {

constexpr int H = 32, SKV = 4096, DH = 192;
constexpr int NCTA = 128;
constexpr int NC = 16;
constexpr int NG = 8;
constexpr int HPC = 4;
constexpr int ROWB = DH * 2;
constexpr int STAGE_B = 64 * ROWB;
constexpr int NS = 8;
constexpr int NSTAGE = 32;
constexpr int DEPTH = 4;
constexpr int TAPER = 29;
constexpr int READ_AT = 10;
constexpr int NV = 6;
constexpr int NWARPS = 1 + NV + 4 + 1;

constexpr int TILE_B = 64 * 128;
constexpr int OFF_X = NS * STAGE_B;
constexpr int OFF_W = OFF_X + 2 * TILE_B;
constexpr int OFF_P = OFF_W + 4096;
constexpr int OFF_S = OFF_P + 1024;
constexpr int OFF_Q = OFF_S + 4096;
constexpr int OFF_O = OFF_Q + 1536;
constexpr int OFF_BAR = OFF_O + 2304;
constexpr int B_FULL = 0, B_FREE = 32 - 6, B_S = 58, B_P = 62, B_W = 66, B_O = 70, B_E = 73, B_F = 74, NBAR = 75;
constexpr int SMEM_BYTES = OFF_BAR + NBAR * 8;

constexpr int SPIN_LIMIT = 1 << 20;

constexpr int ACC_GROUP = 65536;
__device__ unsigned char g_acc[(NG + 1) * ACC_GROUP];
__device__ __forceinline__ int acc_line(int set, int i) {
    return set * 4096 + (i & 1) * 256 + ((i >> 1) & 3) * 1024 + (i >> 3) * 16384;
}

__device__ __forceinline__ uint32_t smem_u32(const void* p) { return (uint32_t)__cvta_generic_to_shared(p); }
__device__ __forceinline__ void mbar_init(uint32_t bar, uint32_t cnt) {
    asm volatile("mbarrier.init.shared::cta.b64 [%0], %1;" :: "r"(bar), "r"(cnt) : "memory");
}
__device__ __forceinline__ void mbar_arm(uint32_t bar, uint32_t bytes) {
    mbar_init(bar, 1);
    asm volatile("mbarrier.arrive.expect_tx.shared::cta.b64 _, [%0], %1;" :: "r"(bar), "r"(bytes) : "memory");
}
__device__ __forceinline__ void mbar_arrive(uint32_t bar, uint32_t n = 1) {
    asm volatile("mbarrier.arrive.shared::cta.b64 _, [%0], %1;" :: "r"(bar), "r"(n) : "memory");
}
__device__ __forceinline__ void mbar_wait(uint32_t bar) {
    asm volatile("{\n.reg .pred p, q;\n.reg .u32 n;\nmov.u32 n, 0;\n"
                 "LF_WAIT_%=:\n"
                 "mbarrier.try_wait.parity.shared::cta.b64 p, [%0], 0;\n"
                 "add.u32 n, n, 1;\n"
                 "setp.lt.u32 q, n, %1;\n"
                 "and.pred q, q, !p;\n"
                 "@q bra LF_WAIT_%=;\n}"
                 :: "r"(bar), "n"(SPIN_LIMIT) : "memory");
}
constexpr uint64_t EVICT_FIRST = 0x12F0000000000000ull;
__device__ __forceinline__ void bulk_g2s(uint32_t dst, const void* src, uint32_t bytes, uint32_t bar) {
    asm volatile("cp.async.bulk.shared::cluster.global.mbarrier::complete_tx::bytes.L2::cache_hint [%0], [%1], %2, [%3], %4;"
                 :: "r"(dst), "l"(src), "r"(bytes), "r"(bar), "l"(EVICT_FIRST) : "memory");
}
__device__ __forceinline__ void tile_g2s(uint32_t dst, const CUtensorMap* map, int n0, uint32_t bar) {
    asm volatile("cp.async.bulk.tensor.2d.shared::cluster.global.mbarrier::complete_tx::bytes [%0], [%1, {%2, %3}], [%4];"
                 :: "r"(dst), "l"(map), "r"(n0), "r"(0), "r"(bar) : "memory");
}
__device__ __forceinline__ void lines_g2s(uint32_t dst, const CUtensorMap* map, int line0, uint32_t bar) {
    asm volatile("cp.async.bulk.tensor.2d.shared::cluster.global.mbarrier::complete_tx::bytes.L2::cache_hint [%0], [%1, {%2, %3}], [%4], %5;"
                 :: "r"(dst), "l"(map), "r"(0), "r"(line0), "r"(bar), "l"(EVICT_FIRST) : "memory");
}
__device__ __forceinline__ bool elect() {
    uint32_t p;
    asm volatile("{\n.reg .pred P;\nelect.sync _|P, 0xffffffff;\nselp.u32 %0, 1, 0, P;\n}" : "=r"(p));
    return p;
}
__device__ __forceinline__ void mma(float (&d)[4], uint32_t a0, uint32_t a1, uint32_t a2, uint32_t a3, uint32_t b0, uint32_t b1) {
    asm volatile("mma.sync.aligned.m16n8k16.row.col.f32.bf16.bf16.f32 {%0,%1,%2,%3}, {%4,%5,%6,%7}, {%8,%9}, {%0,%1,%2,%3};"
                 : "+f"(d[0]), "+f"(d[1]), "+f"(d[2]), "+f"(d[3])
                 : "r"(a0), "r"(a1), "r"(a2), "r"(a3), "r"(b0), "r"(b1));
}
template <int N>
__device__ __forceinline__ void zero(float (&d)[N][4]) {
#pragma unroll
    for (int i = 0; i < N; i++) d[i][0] = d[i][1] = d[i][2] = d[i][3] = 0.f;
}
__device__ __forceinline__ uint4 lds128(uint32_t addr) {
    uint4 v;
    asm volatile("ld.shared.v4.u32 {%0,%1,%2,%3}, [%4];" : "=r"(v.x), "=r"(v.y), "=r"(v.z), "=r"(v.w) : "r"(addr) : "memory");
    return v;
}
__device__ __forceinline__ float2 lds64f(uint32_t addr) {
    float2 v;
    asm volatile("ld.shared.v2.f32 {%0,%1}, [%2];" : "=f"(v.x), "=f"(v.y) : "r"(addr) : "memory");
    return v;
}
__device__ __forceinline__ uint32_t lds32(uint32_t addr) {
    uint32_t v;
    asm volatile("ld.shared.u32 %0, [%1];" : "=r"(v) : "r"(addr) : "memory");
    return v;
}
__device__ __forceinline__ void sts64(uint32_t addr, uint32_t x, uint32_t y) {
    asm volatile("st.shared.v2.u32 [%0], {%1,%2};" :: "r"(addr), "r"(x), "r"(y) : "memory");
}
__device__ __forceinline__ void sts32(uint32_t addr, float x) {
    asm volatile("st.shared.f32 [%0], %1;" :: "r"(addr), "f"(x) : "memory");
}
__device__ __forceinline__ uint4 ldsm4t(uint32_t addr) {
    uint4 v;
    asm volatile("ldmatrix.sync.aligned.m8n8.x4.trans.shared.b16 {%0,%1,%2,%3}, [%4];"
                 : "=r"(v.x), "=r"(v.y), "=r"(v.z), "=r"(v.w) : "r"(addr) : "memory");
    return v;
}
__device__ __forceinline__ float fsel(float a, float b, uint32_t pick_b) {
    float r;
    asm("{\n.reg .pred s;\nsetp.ne.u32 s, %3, 0;\nselp.f32 %0, %2, %1, s;\n}" : "=f"(r) : "f"(a), "f"(b), "r"(pick_b));
    return r;
}
__device__ __forceinline__ uint32_t pack_bf16(float x, float y) {
    uint32_t r;
    asm("cvt.rn.bf16x2.f32 %0, %1, %2;" : "=r"(r) : "f"(y), "f"(x));
    return r;
}
__device__ __forceinline__ void split2(float x, float y, uint32_t& hi, uint32_t& lo) {
    hi = pack_bf16(x, y);
    lo = pack_bf16(x - __uint_as_float(hi << 16), y - __uint_as_float(hi & 0xffff0000u));
}
__device__ __forceinline__ uint32_t word(const uint4& v, int i) { return i == 0 ? v.x : i == 1 ? v.y : i == 2 ? v.z : v.w; }

__device__ __forceinline__ float4 atom_add4(void* p, float x, float y, float z, float w) {
    float4 r;
    asm volatile("atom.relaxed.gpu.global.add.v4.f32 {%0,%1,%2,%3}, [%4], {%5,%6,%7,%8};"
                 : "=f"(r.x), "=f"(r.y), "=f"(r.z), "=f"(r.w) : "l"(p), "f"(x), "f"(y), "f"(z), "f"(w) : "memory");
    return r;
}
__device__ __forceinline__ void red_add4(void* p, float x, float y, float z, float w) {
    asm volatile("red.relaxed.gpu.global.add.v4.f32 [%0], {%1,%2,%3,%4};" :: "l"(p), "f"(x), "f"(y), "f"(z), "f"(w) : "memory");
}
__device__ __forceinline__ float4 ld_relaxed16(const void* p) {
    float4 r;
    asm volatile("{\n.reg .b128 u;\n.reg .b64 a, b;\nld.relaxed.gpu.global.b128 u, [%4];\nmov.b128 {a, b}, u;\n"
                 "mov.b64 {%0, %1}, a;\nmov.b64 {%2, %3}, b;\n}"
                 : "=f"(r.x), "=f"(r.y), "=f"(r.z), "=f"(r.w) : "l"(p) : "memory");
    return r;
}
__device__ __forceinline__ void clear16(void* p) {
    asm volatile("st.global.v4.u32 [%0], {%1,%1,%1,%1};" :: "l"(p), "r"(0) : "memory");
}

__global__ void __launch_bounds__(NWARPS * 32, 1)
linformer_decode_kernel(const __nv_bfloat16* __restrict__ k, const __nv_bfloat16* __restrict__ q,
                        __nv_bfloat16* __restrict__ out, unsigned char* __restrict__ acc_all,
                        const __grid_constant__ CUtensorMap vmap, const __grid_constant__ CUtensorMap emap,
                        const __grid_constant__ CUtensorMap fmap) {
    extern __shared__ __align__(1024) unsigned char smem[];
    const uint32_t sb = smem_u32(smem);
    const uint32_t bars = sb + OFF_BAR;
    const int grp = blockIdx.x & (NG - 1), c = blockIdx.x >> 3;

    {
        const uint32_t ofs = (grp * SKV + c * 256) * ROWB + (threadIdx.x >> 5) * (STAGE_B / NWARPS);
        if (elect()) asm volatile("cp.async.bulk.prefetch.L2.global [%0], %1;" :: "l"((const char*)k + ofs), "r"(STAGE_B / NWARPS) : "memory");
    }
    if (threadIdx.x < 32) {
        const bool leader = elect();
        const int row0 = grp * SKV + c * 256;
        auto issue_k = [&](int s) {
            const int row = row0 + (s >> 2) * NG * SKV + (s & 3) * 64;
            bulk_g2s(sb + (s & (NS - 1)) * STAGE_B, (const char*)k + (size_t)row * ROWB, STAGE_B, bars + (B_FULL + s) * 8);
        };
        auto issue_v = [&](int s) {
            const int row = row0 + ((s >> 2) & 3) * NG * SKV + (s & 3) * 64;
            lines_g2s(sb + (s & (NS - 1)) * STAGE_B, &vmap, row * 3, bars + (B_FULL + s) * 8);
        };
        if (leader) {
            mbar_arm(bars + B_FULL * 8, STAGE_B);
            issue_k(0);
        }
        __syncthreads();
        if (leader) {
#pragma unroll
            for (int j = 0; j < HPC; j++) bulk_g2s(sb + OFF_Q + j * ROWB, q + (j * NG + grp) * DH, ROWB, bars + B_E * 8);
#pragma unroll
            for (int w = 0; w < 4; w++)
                tile_g2s(sb + (w < 3 ? 6 * STAGE_B + w * TILE_B : OFF_X), &emap, c * 256 + w * 64, bars + B_E * 8);
#pragma unroll
            for (int s = 1; s < DEPTH; s++) issue_k(s);
#pragma unroll
            for (int w = 0; w < 4; w++)
                tile_g2s(sb + (w < 3 ? 7 * STAGE_B + w * TILE_B : OFF_X + TILE_B), &fmap, c * 256 + w * 64, bars + B_F * 8);
#pragma unroll 1
            for (int s = DEPTH; s < NSTAGE; s++) {
                if (s >= 6) mbar_wait(bars + (B_FREE + s) * 8);
                mbar_wait(bars + (B_FULL + s - DEPTH + (s >= TAPER)) * 8);
                if (s < 16) issue_k(s); else issue_v(s);
            }
        }
        return;
    }

    const int warp = __shfl_sync(0xffffffffu, threadIdx.x >> 5, 0), lane = threadIdx.x & 31;
    const int g = lane >> 2, t = lane & 3;
    unsigned char* const acc_g = acc_all + grp * ACC_GROUP;
    auto entry16 = [&](int set, int blk) { return acc_g + acc_line(set, 4 * blk + (lane >> 3)) + (lane & 7) * 16; };

    if (warp <= NV) {
        const int vw = warp - 1;
        if (elect()) {
#pragma unroll
            for (int i = 0; i < 5; i++) {
                const int s = vw * 5 + i;
                mbar_arm(bars + (B_FULL + 1 + s) * 8, STAGE_B);
                if (s < 26) mbar_init(bars + (B_FREE + 6 + s) * 8, NV);
            }
        }
        __syncthreads();

        if (vw < 4) {
            const int w = vw;
            const uint32_t tile = sb + (w < 3 ? 6 * STAGE_B + w * TILE_B : OFF_X);
            uint32_t ef[4][4][4];
            mbar_wait(bars + B_E * 8);
#pragma unroll
            for (int i = 0; i < 8; i++) {
                const uint4 ea = lds128(tile + (i * 8 + g) * 128 + (((2 * t) ^ g) << 4));
                const uint4 eb = lds128(tile + (i * 8 + g) * 128 + (((2 * t + 1) ^ g) << 4));
#pragma unroll
                for (int ks = 0; ks < 4; ks++) { ef[i >> 1][ks][i & 1] = word(ea, ks); ef[i >> 1][ks][2 + (i & 1)] = word(eb, ks); }
            }
            __syncwarp();
            if (lane == 0 && w < 3) mbar_arrive(bars + (B_FREE + 6) * 8, NV / 3);

            const uint32_t krow = sb + ((g & 3) * 16 + (g >> 2) * 8) * ROWB + t * 16;
            const uint32_t kofs0 = krow + (g & 1) * 64, kofs1 = krow + ((g & 1) ^ 1) * 64;
            const uint32_t qofs0 = sb + OFF_Q + t * 16 + (g & 1) * 4 + (g & 2) * 32, qofs1 = qofs0 ^ 64;
            const uint32_t m0 = (g == t) ? 0xffffffffu : 0u, m1 = (g == t + 4) ? 0xffffffffu : 0u;
#pragma unroll 1
            for (int j = 0; j < HPC; j++) {
                const int s = j * 4 + w;
                uint32_t qf[6][2];
#pragma unroll
                for (int i = 0; i < 6; i++) {
                    qf[i][0] = lds32(((i & 1) ? qofs1 : qofs0) + j * ROWB + (i >> 1) * 128);
                    qf[i][1] = lds32(((i & 1) ? qofs1 : qofs0) + j * ROWB + (i >> 1) * 128 + 8);
                }
                const uint32_t slot = (s & (NS - 1)) * STAGE_B;
                mbar_wait(bars + (B_FULL + s) * 8);
                float d[8][4];
                zero(d);
#pragma unroll
                for (int i = 0; i < 6; i++)
#pragma unroll
                    for (int u = 0; u < 8; u++) {
                        const uint4 kv = lds128(((i & 1) ? kofs1 : kofs0) + slot + u * ROWB + (i >> 1) * 128);
                        mma(d[u], kv.x, kv.y, kv.z, kv.w, qf[i][0], qf[i][1]);
                    }
                __syncwarp();
                if (lane == 0) mbar_arrive(bars + (B_FREE + s + NS) * 8, NV);

                float d2[4][4];
                zero(d2);
#pragma unroll
                for (int ks = 0; ks < 4; ks++) {
                    uint32_t hi, lo;
                    split2(d[2 * ks][0] + d[2 * ks][3], d[2 * ks + 1][0] + d[2 * ks + 1][3], hi, lo);
#pragma unroll
                    for (int i = 0; i < 4; i++) mma(d2[i], ef[i][ks][0], ef[i][ks][1], ef[i][ks][2], ef[i][ks][3], hi & m0, hi & m1);
#pragma unroll
                    for (int i = 0; i < 4; i++) mma(d2[i], ef[i][ks][0], ef[i][ks][1], ef[i][ks][2], ef[i][ks][3], lo & m0, lo & m1);
                }
                float x[4], y[4];
#pragma unroll
                for (int i = 0; i < 4; i++) { x[i] = d2[i][0] + d2[i][1]; y[i] = d2[i][2] + d2[i][3]; }
#pragma unroll
                for (int i = 0; i < 2; i++) {
                    x[i] = fsel(x[i], x[i + 2], t & 2) + __shfl_xor_sync(0xffffffffu, fsel(x[i + 2], x[i], t & 2), 2);
                    y[i] = fsel(y[i], y[i + 2], t & 2) + __shfl_xor_sync(0xffffffffu, fsel(y[i + 2], y[i], t & 2), 2);
                }
                const float sx = fsel(x[0], x[1], t & 1) + __shfl_xor_sync(0xffffffffu, fsel(x[1], x[0], t & 1), 1);
                const float sy = fsel(y[0], y[1], t & 1) + __shfl_xor_sync(0xffffffffu, fsel(y[1], y[0], t & 1), 1);
                sts32(sb + OFF_S + (j * 4 + w) * 256 + (16 * t + g) * 4, sx);
                sts32(sb + OFF_S + (j * 4 + w) * 256 + (16 * t + 8 + g) * 4, sy);
                __syncwarp();
                if (lane == 0) mbar_arrive(bars + (B_S + j) * 8);
            }
        }

        const int mat = lane >> 3, mi = lane & 7;
        uint32_t off[2];
#pragma unroll
        for (int u = 0; u < 2; u++) {
            const int cc = vw * 4 + u * 2 + (mat & 1), blk = cc >> 3;
            off[u] = sb + ((mat >> 1) * 8 + mi) * ROWB + blk * 128 + (((cc & 7) ^ ((3 * mi + blk) & 7)) << 4);
        }
        const uint32_t wofs = sb + OFF_W + (g & 1) * 64 + t * 16;
        const int col = vw * 32 + (t & 1) * 16 + (t >> 1) * 8 + g;
        unsigned char* accp = acc_g + acc_line(0, vw * 2 + (lane >> 4)) + (lane & 15) * 8;
        __nv_bfloat16* outp = out + (3 * NG + grp) * DH + col;
        asm volatile("" : "+l"(accp), "+l"(outp), "+r"(off[0]), "+r"(off[1]));

        auto v_head = [&](int j, bool release) {
            float acc[2][4];
            zero(acc);
            mbar_wait(bars + (B_W + j) * 8);
            uint4 wb[8];
#pragma unroll
            for (int i = 0; i < 8; i++) wb[i] = lds128(wofs + j * 1024 + i * 128);
            const uint32_t slot0 = (j & 1) * 4 * STAGE_B;
#pragma unroll
            for (int sub = 0; sub < 4; sub++) {
                const int s = 16 + j * 4 + sub;
                mbar_wait(bars + (B_FULL + s) * 8);
#pragma unroll
                for (int x = sub * 4; x < sub * 4 + 4; x++)
#pragma unroll
                    for (int u = 0; u < 2; u++) {
                        const uint4 a = ldsm4t(off[u] + slot0 + x * 16 * ROWB);
                        mma(acc[u], a.x, a.y, a.z, a.w, word(wb[x >> 1], (x & 1) * 2), word(wb[x >> 1], (x & 1) * 2 + 1));
                    }
                if (release) {
                    __syncwarp();
                    if (lane == 0) mbar_arrive(bars + (B_FREE + s + NS) * 8);
                }
            }
            return fsel(fsel(acc[0][0] + acc[0][1], acc[0][2] + acc[0][3], t & 2),
                        fsel(acc[1][0] + acc[1][1], acc[1][2] + acc[1][3], t & 2), t & 1);
        };
#pragma unroll 1
        for (int j = 0; j < HPC - 1; j++) {
            sts32(sb + OFF_O + (j * DH + col) * 4, v_head(j, j < 2));
            __syncwarp();
            if (lane == 0) mbar_arrive(bars + (B_O + j) * 8);
        }
        const float ov = v_head(HPC - 1, false);
        float tot, cnt;
        asm volatile("atom.relaxed.gpu.global.add.v2.f32 {%0, %1}, [%2], {%3, 0f3F800000};"
                     : "=f"(tot), "=f"(cnt) : "l"(accp), "f"(ov) : "memory");
        asm volatile("{\n.reg .pred p;\n.reg .b16 h;\n"
                     "cvt.rn.bf16.f32 h, %2;\n"
                     "setp.eq.f32 p, %3, %4;\n"
                     "@p st.global.b16 [%1], h;\n"
                     "@p st.global.v2.u32 [%0], {0, 0};\n}"
                     :: "l"(accp), "l"(outp), "f"(tot + ov), "f"(cnt), "f"((float)(NC - 1)) : "memory");
    } else if (warp <= NV + 4) {
        const int w = warp - (NV + 1);
        const uint32_t tile = sb + (w < 3 ? 7 * STAGE_B + w * TILE_B : OFF_X + TILE_B);
        if (elect()) {
            mbar_init(bars + (B_S + w) * 8, 4);
            mbar_init(bars + (B_P + w) * 8, 1);
            mbar_init(bars + (B_W + w) * 8, 4);
        }
        __syncthreads();
        uint4 fr[16];
        mbar_wait(bars + B_F * 8);
#pragma unroll
        for (int i = 0; i < 16; i++)
            fr[i] = lds128(tile + ((i >> 1) * 8 + 2 * t + (i & 1)) * 128 + ((g ^ (2 * t + (i & 1))) << 4));
        __syncwarp();
        if (lane == 0 && w < 3) mbar_arrive(bars + (B_FREE + 7) * 8, NV / 3);
        uint32_t fb[8][8];
#pragma unroll
        for (int i = 0; i < 8; i++)
#pragma unroll
            for (int x = 0; x < 8; x++)
                fb[i][x] = __byte_perm(word(fr[2 * x], i >> 1), word(fr[2 * x + 1], i >> 1), (i & 1) ? 0x7632 : 0x5410);

#pragma unroll 1
        for (int j = 0; j < HPC; j++) {
            if (j == w) {
                mbar_wait(bars + (B_FULL + READ_AT + 4 * j) * 8);
                float4 sc;
#pragma unroll 1
                for (int it = 0;; it++) {
                    sc = ld_relaxed16(entry16(2, j));
                    if (__all_sync(0xffffffffu, sc.z == (float)NC)) break;
                    if (it > SPIN_LIMIT) __trap();
                    __nanosleep(500);
                }
                const float scale = 0.07216878364870322f;
                sc.x *= scale; sc.y *= scale;
                float m = fmaxf(sc.x, sc.y);
#pragma unroll
                for (int o = 16; o > 0; o >>= 1) m = fmaxf(m, __shfl_xor_sync(0xffffffffu, m, o));
                const float e0 = expf(sc.x - m), e1 = expf(sc.y - m);
                float sum = e0 + e1;
#pragma unroll
                for (int o = 16; o > 0; o >>= 1) sum += __shfl_xor_sync(0xffffffffu, sum, o);
                uint32_t hi, lo;
                split2(e0 / sum, e1 / sum, hi, lo);
                sts64(sb + OFF_P + j * 256 + (g >> 1) * 64 + t * 16 + (g & 1) * 8, hi, lo);
                __syncwarp();
                if (lane == 0) mbar_arrive(bars + (B_P + j) * 8);
            }
            mbar_wait(bars + (B_P + j) * 8);
            float d[8][4];
            zero(d);
#pragma unroll
            for (int ks = 0; ks < 4; ks++) {
                const uint4 a = lds128(sb + OFF_P + j * 256 + ks * 64 + t * 16);
#pragma unroll
                for (int i = 0; i < 8; i++) mma(d[i], a.x, a.y, a.z, a.w, fb[i][2 * ks], fb[i][2 * ks + 1]);
            }
            float x[8], y[8];
#pragma unroll
            for (int i = 0; i < 8; i++) { x[i] = d[i][0] + d[i][2]; y[i] = d[i][1] + d[i][3]; }
#pragma unroll
            for (int i = 0; i < 4; i++) { x[i] = fsel(x[i], x[i + 4], g & 4); y[i] = fsel(y[i], y[i + 4], g & 4); }
#pragma unroll
            for (int i = 0; i < 2; i++) { x[i] = fsel(x[i], x[i + 2], g & 2); y[i] = fsel(y[i], y[i + 2], g & 2); }
            uint32_t xh, xl, yh, yl;
            split2(x[0], x[1], xh, xl);
            split2(y[0], y[1], yh, yl);
            sts64(sb + OFF_W + (j * 4 + w) * 256 + (t >> 1) * 128 + (g & 1) * 64 + (g >> 1) * 16 + (t & 1) * 8,
                  (g & 1) ? xl : xh, (g & 1) ? yl : yh);
            __syncwarp();
            if (lane == 0) mbar_arrive(bars + (B_W + j) * 8);
        }
    } else {
        if (elect()) {
            asm volatile("prefetch.tensormap [%0];" :: "l"(&emap) : "memory");
            asm volatile("prefetch.tensormap [%0];" :: "l"(&fmap) : "memory");
            asm volatile("prefetch.tensormap [%0];" :: "l"(&vmap) : "memory");
            mbar_arm(bars + B_E * 8, 4 * TILE_B + HPC * ROWB);
            mbar_arm(bars + B_F * 8, 4 * TILE_B);
            mbar_arm(bars + (B_FULL + 31) * 8, STAGE_B);
#pragma unroll
            for (int j = 0; j < 3; j++) mbar_init(bars + (B_O + j) * 8, NV);
        }
        __syncthreads();
#pragma unroll 1
        for (int j = 0; j < HPC; j++) {
            mbar_wait(bars + (B_S + j) * 8);
            const float2 p0 = lds64f(sb + OFF_S + (j * 4 + 0) * 256 + lane * 8);
            const float2 p1 = lds64f(sb + OFF_S + (j * 4 + 1) * 256 + lane * 8);
            const float2 p2 = lds64f(sb + OFF_S + (j * 4 + 2) * 256 + lane * 8);
            const float2 p3 = lds64f(sb + OFF_S + (j * 4 + 3) * 256 + lane * 8);
            red_add4(entry16(2, j), (p0.x + p1.x) + (p2.x + p3.x), (p0.y + p1.y) + (p2.y + p3.y), 1.f, 0.f);
        }
#pragma unroll 1
        for (int j = 0; j < HPC - 1; j++) {
            mbar_wait(bars + (B_P + j + 1) * 8);
            mbar_wait(bars + (B_O + j) * 8);
            __nv_bfloat16* op = out + (j * NG + grp) * DH + lane;
            float o[2][3];
            float4 r[2];
#pragma unroll
            for (int i = 0; i < 2; i++) {
#pragma unroll
                for (int x = 0; x < 3; x++) o[i][x] = __uint_as_float(lds32(sb + OFF_O + (j * DH + (i * 3 + x) * 32 + lane) * 4));
                r[i] = atom_add4(entry16(1, 2 * j + i), o[i][0], o[i][1], o[i][2], 1.f);
            }
#pragma unroll
            for (int i = 0; i < 2; i++)
                if (r[i].w == (float)(NC - 1)) {
                    op[i * 96] = __float2bfloat16(r[i].x + o[i][0]);
                    op[i * 96 + 32] = __float2bfloat16(r[i].y + o[i][1]);
                    op[i * 96 + 64] = __float2bfloat16(r[i].z + o[i][2]);
                    clear16(entry16(1, 2 * j + i));
                    if (i == 1 || j == 0) clear16(entry16(2, j + i));
                }
        }
    }
}

static CUtensorMap make_map(const void* p, uint64_t inner, uint64_t rows, uint32_t box_rows) {
    typedef CUresult (*EncodeFn)(CUtensorMap*, CUtensorMapDataType, cuuint32_t, void*, const cuuint64_t*, const cuuint64_t*,
                                 const cuuint32_t*, const cuuint32_t*, CUtensorMapInterleave, CUtensorMapSwizzle,
                                 CUtensorMapL2promotion, CUtensorMapFloatOOBfill);
    void* fn = nullptr;
    cudaDriverEntryPointQueryResult qr;
    cudaGetDriverEntryPoint("cuTensorMapEncodeTiled", &fn, cudaEnableDefault, &qr);
    CUtensorMap m;
    const cuuint64_t dims[2] = {inner, rows};
    const cuuint64_t strides[1] = {inner * 2};
    const cuuint32_t box[2] = {64, box_rows};
    const cuuint32_t estr[2] = {1, 1};
    ((EncodeFn)fn)(&m, CU_TENSOR_MAP_DATA_TYPE_BFLOAT16, 2, (void*)p, dims, strides, box, estr, CU_TENSOR_MAP_INTERLEAVE_NONE,
                   CU_TENSOR_MAP_SWIZZLE_128B, CU_TENSOR_MAP_L2_PROMOTION_NONE, CU_TENSOR_MAP_FLOAT_OOB_FILL_NONE);
    return m;
}

}

extern "C" void kernel_launch(void* const* d_in, const int* in_sizes, int n_in, void* d_out, int out_size) {
    using namespace lf;
    void* acc = nullptr;
    cudaGetSymbolAddress(&acc, g_acc);
    acc = (void*)(((uintptr_t)acc + ACC_GROUP - 1) & ~(uintptr_t)(ACC_GROUP - 1));
    cudaFuncSetAttribute(linformer_decode_kernel, cudaFuncAttributeMaxDynamicSharedMemorySize, SMEM_BYTES);
    linformer_decode_kernel<<<NCTA, NWARPS * 32, SMEM_BYTES>>>(
        (const __nv_bfloat16*)d_in[1], (const __nv_bfloat16*)d_in[0], (__nv_bfloat16*)d_out, (unsigned char*)acc,
        make_map(d_in[2], 64, (uint64_t)H * SKV * 3, 192),
        make_map(d_in[3], SKV, 64, 64), make_map(d_in[4], SKV, 64, 64));
}
```

```cpp
#include <cuda.h>
#include <cuda_runtime.h>
#include <cuda_bf16.h>
#include <stdint.h>

namespace lf {

constexpr int H = 32, SKV = 4096, DH = 192;
constexpr int NCTA = 128;
constexpr int NC = 16;
constexpr int NG = 8;
constexpr int HPC = 4;
constexpr int ROWB = DH * 2;
constexpr int STAGE_B = 64 * ROWB;
constexpr int NS = 8;
constexpr int NSTAGE = 32;
constexpr int DEPTH = 4;
constexpr int TAPER = 29;
constexpr int READ_AT = 10;
constexpr int NV = 6;
constexpr int NWARPS = 1 + NV + 4 + 1;

constexpr int TILE_B = 64 * 128;
constexpr int OFF_X = NS * STAGE_B;
constexpr int OFF_W = OFF_X + 2 * TILE_B;
constexpr int OFF_P = OFF_W + 4096;
constexpr int OFF_S = OFF_P + 1024;
constexpr int OFF_Q = OFF_S + 4096;
constexpr int OFF_O = OFF_Q + 1536;
constexpr int OFF_BAR = OFF_O + 2304;
constexpr int B_FULL = 0, B_FREE = 32 - 6, B_S = 58, B_P = 62, B_W = 66, B_O = 70, B_E = 73, B_F = 74, NBAR = 75;
constexpr int SMEM_BYTES = OFF_BAR + NBAR * 8;

constexpr int SPIN_LIMIT = 1 << 20;

constexpr int ACC_GROUP = 65536;
__device__ unsigned char g_acc[(NG + 1) * ACC_GROUP];
__device__ __forceinline__ int acc_line(int set, int i) {
    return set * 4096 + (i & 1) * 256 + ((i >> 1) & 3) * 1024 + (i >> 3) * 16384;
}

__device__ __forceinline__ uint32_t smem_u32(const void* p) { return (uint32_t)__cvta_generic_to_shared(p); }
__device__ __forceinline__ void mbar_init(uint32_t bar, uint32_t cnt) {
    asm volatile("mbarrier.init.shared::cta.b64 [%0], %1;" :: "r"(bar), "r"(cnt) : "memory");
}
__device__ __forceinline__ void mbar_arm(uint32_t bar, uint32_t bytes) {
    mbar_init(bar, 1);
    asm volatile("mbarrier.arrive.expect_tx.shared::cta.b64 _, [%0], %1;" :: "r"(bar), "r"(bytes) : "memory");
}
__device__ __forceinline__ void mbar_arrive(uint32_t bar, uint32_t n = 1) {
    asm volatile("mbarrier.arrive.shared::cta.b64 _, [%0], %1;" :: "r"(bar), "r"(n) : "memory");
}
__device__ __forceinline__ void mbar_wait(uint32_t bar) {
    asm volatile("{\n.reg .pred p, q;\n.reg .u32 n;\nmov.u32 n, 0;\n"
                 "LF_WAIT_%=:\n"
                 "mbarrier.try_wait.parity.shared::cta.b64 p, [%0], 0;\n"
                 "add.u32 n, n, 1;\n"
                 "setp.lt.u32 q, n, %1;\n"
                 "and.pred q, q, !p;\n"
                 "@q bra LF_WAIT_%=;\n}"
                 :: "r"(bar), "n"(SPIN_LIMIT) : "memory");
}
constexpr uint64_t EVICT_FIRST = 0x12F0000000000000ull;
__device__ __forceinline__ void bulk_g2s(uint32_t dst, const void* src, uint32_t bytes, uint32_t bar) {
    asm volatile("cp.async.bulk.shared::cluster.global.mbarrier::complete_tx::bytes.L2::cache_hint [%0], [%1], %2, [%3], %4;"
                 :: "r"(dst), "l"(src), "r"(bytes), "r"(bar), "l"(EVICT_FIRST) : "memory");
}
__device__ __forceinline__ void tile_g2s(uint32_t dst, const CUtensorMap* map, int n0, uint32_t bar) {
    asm volatile("cp.async.bulk.tensor.2d.shared::cluster.global.mbarrier::complete_tx::bytes [%0], [%1, {%2, %3}], [%4];"
                 :: "r"(dst), "l"(map), "r"(n0), "r"(0), "r"(bar) : "memory");
}
__device__ __forceinline__ void lines_g2s(uint32_t dst, const CUtensorMap* map, int line0, uint32_t bar) {
    asm volatile("cp.async.bulk.tensor.2d.shared::cluster.global.mbarrier::complete_tx::bytes.L2::cache_hint [%0], [%1, {%2, %3}], [%4], %5;"
                 :: "r"(dst), "l"(map), "r"(0), "r"(line0), "r"(bar), "l"(EVICT_FIRST) : "memory");
}
__device__ __forceinline__ bool elect() {
    uint32_t p;
    asm volatile("{\n.reg .pred P;\nelect.sync _|P, 0xffffffff;\nselp.u32 %0, 1, 0, P;\n}" : "=r"(p));
    return p;
}
__device__ __forceinline__ void mma(float (&d)[4], uint32_t a0, uint32_t a1, uint32_t a2, uint32_t a3, uint32_t b0, uint32_t b1) {
    asm volatile("mma.sync.aligned.m16n8k16.row.col.f32.bf16.bf16.f32 {%0,%1,%2,%3}, {%4,%5,%6,%7}, {%8,%9}, {%0,%1,%2,%3};"
                 : "+f"(d[0]), "+f"(d[1]), "+f"(d[2]), "+f"(d[3])
                 : "r"(a0), "r"(a1), "r"(a2), "r"(a3), "r"(b0), "r"(b1));
}
template <int N>
__device__ __forceinline__ void zero(float (&d)[N][4]) {
#pragma unroll
    for (int i = 0; i < N; i++) d[i][0] = d[i][1] = d[i][2] = d[i][3] = 0.f;
}
__device__ __forceinline__ uint4 lds128(uint32_t addr) {
    uint4 v;
    asm volatile("ld.shared.v4.u32 {%0,%1,%2,%3}, [%4];" : "=r"(v.x), "=r"(v.y), "=r"(v.z), "=r"(v.w) : "r"(addr) : "memory");
    return v;
}
__device__ __forceinline__ float2 lds64f(uint32_t addr) {
    float2 v;
    asm volatile("ld.shared.v2.f32 {%0,%1}, [%2];" : "=f"(v.x), "=f"(v.y) : "r"(addr) : "memory");
    return v;
}
__device__ __forceinline__ uint32_t lds32(uint32_t addr) {
    uint32_t v;
    asm volatile("ld.shared.u32 %0, [%1];" : "=r"(v) : "r"(addr) : "memory");
    return v;
}
__device__ __forceinline__ void sts64(uint32_t addr, uint32_t x, uint32_t y) {
    asm volatile("st.shared.v2.u32 [%0], {%1,%2};" :: "r"(addr), "r"(x), "r"(y) : "memory");
}
__device__ __forceinline__ void sts32(uint32_t addr, float x) {
    asm volatile("st.shared.f32 [%0], %1;" :: "r"(addr), "f"(x) : "memory");
}
__device__ __forceinline__ uint4 ldsm4t(uint32_t addr) {
    uint4 v;
    asm volatile("ldmatrix.sync.aligned.m8n8.x4.trans.shared.b16 {%0,%1,%2,%3}, [%4];"
                 : "=r"(v.x), "=r"(v.y), "=r"(v.z), "=r"(v.w) : "r"(addr) : "memory");
    return v;
}
__device__ __forceinline__ float fsel(float a, float b, uint32_t pick_b) {
    float r;
    asm("{\n.reg .pred s;\nsetp.ne.u32 s, %3, 0;\nselp.f32 %0, %2, %1, s;\n}" : "=f"(r) : "f"(a), "f"(b), "r"(pick_b));
    return r;
}
__device__ __forceinline__ uint32_t pack_bf16(float x, float y) {
    uint32_t r;
    asm("cvt.rn.bf16x2.f32 %0, %1, %2;" : "=r"(r) : "f"(y), "f"(x));
    return r;
}
__device__ __forceinline__ void split2(float x, float y, uint32_t& hi, uint32_t& lo) {
    hi = pack_bf16(x, y);
    lo = pack_bf16(x - __uint_as_float(hi << 16), y - __uint_as_float(hi & 0xffff0000u));
}
__device__ __forceinline__ uint32_t word(const uint4& v, int i) { return i == 0 ? v.x : i == 1 ? v.y : i == 2 ? v.z : v.w; }

__device__ __forceinline__ float4 atom_add4(void* p, float x, float y, float z, float w) {
    float4 r;
    asm volatile("atom.relaxed.gpu.global.add.v4.f32 {%0,%1,%2,%3}, [%4], {%5,%6,%7,%8};"
                 : "=f"(r.x), "=f"(r.y), "=f"(r.z), "=f"(r.w) : "l"(p), "f"(x), "f"(y), "f"(z), "f"(w) : "memory");
    return r;
}
__device__ __forceinline__ void red_add4(void* p, float x, float y, float z, float w) {
    asm volatile("red.relaxed.gpu.global.add.v4.f32 [%0], {%1,%2,%3,%4};" :: "l"(p), "f"(x), "f"(y), "f"(z), "f"(w) : "memory");
}
__device__ __forceinline__ float4 ld_relaxed16(const void* p) {
    float4 r;
    asm volatile("{\n.reg .b128 u;\n.reg .b64 a, b;\nld.relaxed.gpu.global.b128 u, [%4];\nmov.b128 {a, b}, u;\n"
                 "mov.b64 {%0, %1}, a;\nmov.b64 {%2, %3}, b;\n}"
                 : "=f"(r.x), "=f"(r.y), "=f"(r.z), "=f"(r.w) : "l"(p) : "memory");
    return r;
}
__device__ __forceinline__ void clear16(void* p) {
    asm volatile("st.global.v4.u32 [%0], {%1,%1,%1,%1};" :: "l"(p), "r"(0) : "memory");
}

__global__ void __launch_bounds__(NWARPS * 32, 1)
linformer_decode_kernel(const __nv_bfloat16* __restrict__ k, const __nv_bfloat16* __restrict__ q,
                        __nv_bfloat16* __restrict__ out, unsigned char* __restrict__ acc_all,
                        const __grid_constant__ CUtensorMap vmap, const __grid_constant__ CUtensorMap emap,
                        const __grid_constant__ CUtensorMap fmap) {
    extern __shared__ __align__(1024) unsigned char smem[];
    const uint32_t sb = smem_u32(smem);
    const uint32_t bars = sb + OFF_BAR;
    const int grp = blockIdx.x & (NG - 1), c = blockIdx.x >> 3;

    {
        const uint32_t ofs = (grp * SKV + c * 256) * ROWB + (threadIdx.x >> 5) * (STAGE_B / NWARPS);
        if (elect()) asm volatile("cp.async.bulk.prefetch.L2.global [%0], %1;" :: "l"((const char*)k + ofs), "r"(STAGE_B / NWARPS) : "memory");
    }
    if (threadIdx.x < 32) {
        const bool leader = elect();
        const int row0 = grp * SKV + c * 256;
        auto issue_k = [&](int s) {
            const int row = row0 + (s >> 2) * NG * SKV + (s & 3) * 64;
            bulk_g2s(sb + (s & (NS - 1)) * STAGE_B, (const char*)k + (size_t)row * ROWB, STAGE_B, bars + (B_FULL + s) * 8);
        };
        auto issue_v = [&](int s) {
            const int row = row0 + ((s >> 2) & 3) * NG * SKV + (s & 3) * 64;
            lines_g2s(sb + (s & (NS - 1)) * STAGE_B, &vmap, row * 3, bars + (B_FULL + s) * 8);
        };
        if (leader) {
            mbar_arm(bars + B_FULL * 8, STAGE_B);
            issue_k(0);
        }
        __syncthreads();
        if (leader) {
#pragma unroll
            for (int j = 0; j < HPC; j++) bulk_g2s(sb + OFF_Q + j * ROWB, q + (j * NG + grp) * DH, ROWB, bars + B_E * 8);
#pragma unroll
            for (int w = 0; w < 4; w++)
                tile_g2s(sb + (w < 3 ? 6 * STAGE_B + w * TILE_B : OFF_X), &emap, c * 256 + w * 64, bars + B_E * 8);
#pragma unroll
            for (int s = 1; s < DEPTH; s++) issue_k(s);
#pragma unroll
            for (int w = 0; w < 4; w++)
                tile_g2s(sb + (w < 3 ? 7 * STAGE_B + w * TILE_B : OFF_X + TILE_B), &fmap, c * 256 + w * 64, bars + B_F * 8);
#pragma unroll 1
            for (int s = DEPTH; s < NSTAGE; s++) {
                if (s >= 6) mbar_wait(bars + (B_FREE + s) * 8);
                mbar_wait(bars + (B_FULL + s - DEPTH + (s >= TAPER)) * 8);
                if (s < 16) issue_k(s); else issue_v(s);
            }
        }
        return;
    }

    const int warp = __shfl_sync(0xffffffffu, threadIdx.x >> 5, 0), lane = threadIdx.x & 31;
    const int g = lane >> 2, t = lane & 3;
    unsigned char* const acc_g = acc_all + grp * ACC_GROUP;
    auto entry16 = [&](int set, int blk) { return acc_g + acc_line(set, 4 * blk + (lane >> 3)) + (lane & 7) * 16; };

    if (warp <= NV) {
        const int vw = warp - 1;
        if (elect()) {
#pragma unroll
            for (int i = 0; i < 5; i++) {
                const int s = vw * 5 + i;
                mbar_arm(bars + (B_FULL + 1 + s) * 8, STAGE_B);
                if (s < 26) mbar_init(bars + (B_FREE + 6 + s) * 8, NV);
            }
        }
        __syncthreads();

        if (vw < 4) {
            const int w = vw;
            const uint32_t tile = sb + (w < 3 ? 6 * STAGE_B + w * TILE_B : OFF_X);
            uint32_t ef[4][4][4];
            mbar_wait(bars + B_E * 8);
#pragma unroll
            for (int i = 0; i < 8; i++) {
                const uint4 ea = lds128(tile + (i * 8 + g) * 128 + (((2 * t) ^ g) << 4));
                const uint4 eb = lds128(tile + (i * 8 + g) * 128 + (((2 * t + 1) ^ g) << 4));
#pragma unroll
                for (int ks = 0; ks < 4; ks++) { ef[i >> 1][ks][i & 1] = word(ea, ks); ef[i >> 1][ks][2 + (i & 1)] = word(eb, ks); }
            }
            __syncwarp();
            if (lane == 0 && w < 3) mbar_arrive(bars + (B_FREE + 6) * 8, NV / 3);

            const uint32_t krow = sb + ((g & 3) * 16 + (g >> 2) * 8) * ROWB + t * 16;
            const uint32_t kofs0 = krow + (g & 1) * 64, kofs1 = krow + ((g & 1) ^ 1) * 64;
            const uint32_t qofs0 = sb + OFF_Q + t * 16 + (g & 1) * 4 + (g & 2) * 32, qofs1 = qofs0 ^ 64;
            const uint32_t m0 = (g == t) ? 0xffffffffu : 0u, m1 = (g == t + 4) ? 0xffffffffu : 0u;
#pragma unroll 1
            for (int j = 0; j < HPC; j++) {
                const int s = j * 4 + w;
                uint32_t qf[6][2];
#pragma unroll
                for (int i = 0; i < 6; i++) {
                    qf[i][0] = lds32(((i & 1) ? qofs1 : qofs0) + j * ROWB + (i >> 1) * 128);
                    qf[i][1] = lds32(((i & 1) ? qofs1 : qofs0) + j * ROWB + (i >> 1) * 128 + 8);
                }
                const uint32_t slot = (s & (NS - 1)) * STAGE_B;
                mbar_wait(bars + (B_FULL + s) * 8);
                float d[8][4];
                zero(d);
#pragma unroll
                for (int i = 0; i < 6; i++)
#pragma unroll
                    for (int u = 0; u < 8; u++) {
                        const uint4 kv = lds128(((i & 1) ? kofs1 : kofs0) + slot + u * ROWB + (i >> 1) * 128);
                        mma(d[u], kv.x, kv.y, kv.z, kv.w, qf[i][0], qf[i][1]);
                    }
                __syncwarp();
                if (lane == 0) mbar_arrive(bars + (B_FREE + s + NS) * 8, NV);

                float d2[4][4];
                zero(d2);
#pragma unroll
                for (int ks = 0; ks < 4; ks++) {
                    uint32_t hi, lo;
                    split2(d[2 * ks][0] + d[2 * ks][3], d[2 * ks + 1][0] + d[2 * ks + 1][3], hi, lo);
#pragma unroll
                    for (int i = 0; i < 4; i++) mma(d2[i], ef[i][ks][0], ef[i][ks][1], ef[i][ks][2], ef[i][ks][3], hi & m0, hi & m1);
#pragma unroll
                    for (int i = 0; i < 4; i++) mma(d2[i], ef[i][ks][0], ef[i][ks][1], ef[i][ks][2], ef[i][ks][3], lo & m0, lo & m1);
                }
                float x[4], y[4];
#pragma unroll
                for (int i = 0; i < 4; i++) { x[i] = d2[i][0] + d2[i][1]; y[i] = d2[i][2] + d2[i][3]; }
#pragma unroll
                for (int i = 0; i < 2; i++) {
                    x[i] = fsel(x[i], x[i + 2], t & 2) + __shfl_xor_sync(0xffffffffu, fsel(x[i + 2], x[i], t & 2), 2);
                    y[i] = fsel(y[i], y[i + 2], t & 2) + __shfl_xor_sync(0xffffffffu, fsel(y[i + 2], y[i], t & 2), 2);
                }
                const float sx = fsel(x[0], x[1], t & 1) + __shfl_xor_sync(0xffffffffu, fsel(x[1], x[0], t & 1), 1);
                const float sy = fsel(y[0], y[1], t & 1) + __shfl_xor_sync(0xffffffffu, fsel(y[1], y[0], t & 1), 1);
                sts32(sb + OFF_S + (j * 4 + w) * 256 + (16 * t + g) * 4, sx);
                sts32(sb + OFF_S + (j * 4 + w) * 256 + (16 * t + 8 + g) * 4, sy);
                __syncwarp();
                if (lane == 0) mbar_arrive(bars + (B_S + j) * 8);
            }
        }

        const int mat = lane >> 3, mi = lane & 7;
        uint32_t off[2];
#pragma unroll
        for (int u = 0; u < 2; u++) {
            const int cc = vw * 4 + u * 2 + (mat & 1), blk = cc >> 3;
            off[u] = sb + ((mat >> 1) * 8 + mi) * ROWB + blk * 128 + (((cc & 7) ^ ((3 * mi + blk) & 7)) << 4);
        }
        const uint32_t wofs = sb + OFF_W + (g & 1) * 64 + t * 16;
        const int col = vw * 32 + (t & 1) * 16 + (t >> 1) * 8 + g;
        unsigned char* accp = acc_g + acc_line(0, vw * 2 + (lane >> 4)) + (lane & 15) * 8;
        __nv_bfloat16* outp = out + (3 * NG + grp) * DH + col;
        asm volatile("" : "+l"(accp), "+l"(outp), "+r"(off[0]), "+r"(off[1]));

        auto v_head = [&](int j, bool release) {
            float acc[2][4];
            zero(acc);
            mbar_wait(bars + (B_W + j) * 8);
            uint4 wb[8];
#pragma unroll
            for (int i = 0; i < 8; i++) wb[i] = lds128(wofs + j * 1024 + i * 128);
            const uint32_t slot0 = (j & 1) * 4 * STAGE_B;
#pragma unroll
            for (int sub = 0; sub < 4; sub++) {
                const int s = 16 + j * 4 + sub;
                mbar_wait(bars + (B_FULL + s) * 8);
#pragma unroll
                for (int x = sub * 4; x < sub * 4 + 4; x++)
#pragma unroll
                    for (int u = 0; u < 2; u++) {
                        const uint4 a = ldsm4t(off[u] + slot0 + x * 16 * ROWB);
                        mma(acc[u], a.x, a.y, a.z, a.w, word(wb[x >> 1], (x & 1) * 2), word(wb[x >> 1], (x & 1) * 2 + 1));
                    }
                if (release) {
                    __syncwarp();
                    if (lane == 0) mbar_arrive(bars + (B_FREE + s + NS) * 8);
                }
            }
            return fsel(fsel(acc[0][0] + acc[0][1], acc[0][2] + acc[0][3], t & 2),
                        fsel(acc[1][0] + acc[1][1], acc[1][2] + acc[1][3], t & 2), t & 1);
        };
#pragma unroll 1
        for (int j = 0; j < HPC - 1; j++) {
            sts32(sb + OFF_O + (j * DH + col) * 4, v_head(j, j < 2));
            __syncwarp();
            if (lane == 0) mbar_arrive(bars + (B_O + j) * 8);
        }
        const float ov = v_head(HPC - 1, false);
        float tot, cnt;
        asm volatile("atom.relaxed.gpu.global.add.v2.f32 {%0, %1}, [%2], {%3, 0f3F800000};"
                     : "=f"(tot), "=f"(cnt) : "l"(accp), "f"(ov) : "memory");
        asm volatile("{\n.reg .pred p;\n.reg .b16 h;\n"
                     "cvt.rn.bf16.f32 h, %2;\n"
                     "setp.eq.f32 p, %3, %4;\n"
                     "@p st.global.b16 [%1], h;\n"
                     "@p st.global.v2.u32 [%0], {0, 0};\n}"
                     :: "l"(accp), "l"(outp), "f"(tot + ov), "f"(cnt), "f"((float)(NC - 1)) : "memory");
    } else if (warp <= NV + 4) {
        const int w = warp - (NV + 1);
        const uint32_t tile = sb + (w < 3 ? 7 * STAGE_B + w * TILE_B : OFF_X + TILE_B);
        if (elect()) {
            mbar_init(bars + (B_S + w) * 8, 4);
            mbar_init(bars + (B_P + w) * 8, 1);
            mbar_init(bars + (B_W + w) * 8, 4);
        }
        __syncthreads();
        uint4 fr[16];
        mbar_wait(bars + B_F * 8);
#pragma unroll
        for (int i = 0; i < 16; i++)
            fr[i] = lds128(tile + ((i >> 1) * 8 + 2 * t + (i & 1)) * 128 + ((g ^ (2 * t + (i & 1))) << 4));
        __syncwarp();
        if (lane == 0 && w < 3) mbar_arrive(bars + (B_FREE + 7) * 8, NV / 3);
        uint32_t fb[8][8];
#pragma unroll
        for (int i = 0; i < 8; i++)
#pragma unroll
            for (int x = 0; x < 8; x++)
                fb[i][x] = __byte_perm(word(fr[2 * x], i >> 1), word(fr[2 * x + 1], i >> 1), (i & 1) ? 0x7632 : 0x5410);

#pragma unroll 1
        for (int j = 0; j < HPC; j++) {
            if (j == w) {
                mbar_wait(bars + (B_FULL + READ_AT + 4 * j) * 8);
                float4 sc;
#pragma unroll 1
                for (int it = 0;; it++) {
                    sc = ld_relaxed16(entry16(2, j));
                    if (__all_sync(0xffffffffu, sc.z == (float)NC)) break;
                    if (it > SPIN_LIMIT) __trap();
                    __nanosleep(500);
                }
                const float scale = 0.07216878364870322f;
                sc.x *= scale; sc.y *= scale;
                float m = fmaxf(sc.x, sc.y);
#pragma unroll
                for (int o = 16; o > 0; o >>= 1) m = fmaxf(m, __shfl_xor_sync(0xffffffffu, m, o));
                const float e0 = expf(sc.x - m), e1 = expf(sc.y - m);
                float sum = e0 + e1;
#pragma unroll
                for (int o = 16; o > 0; o >>= 1) sum += __shfl_xor_sync(0xffffffffu, sum, o);
                uint32_t hi, lo;
                split2(e0 / sum, e1 / sum, hi, lo);
                sts64(sb + OFF_P + j * 256 + (g >> 1) * 64 + t * 16 + (g & 1) * 8, hi, lo);
                __syncwarp();
                if (lane == 0) mbar_arrive(bars + (B_P + j) * 8);
            }
            mbar_wait(bars + (B_P + j) * 8);
            float d[8][4];
            zero(d);
#pragma unroll
            for (int ks = 0; ks < 4; ks++) {
                const uint4 a = lds128(sb + OFF_P + j * 256 + ks * 64 + t * 16);
#pragma unroll
                for (int i = 0; i < 8; i++) mma(d[i], a.x, a.y, a.z, a.w, fb[i][2 * ks], fb[i][2 * ks + 1]);
            }
            float x[8], y[8];
#pragma unroll
            for (int i = 0; i < 8; i++) { x[i] = d[i][0] + d[i][2]; y[i] = d[i][1] + d[i][3]; }
#pragma unroll
            for (int i = 0; i < 4; i++) { x[i] = fsel(x[i], x[i + 4], g & 4); y[i] = fsel(y[i], y[i + 4], g & 4); }
#pragma unroll
            for (int i = 0; i < 2; i++) { x[i] = fsel(x[i], x[i + 2], g & 2); y[i] = fsel(y[i], y[i + 2], g & 2); }
            uint32_t xh, xl, yh, yl;
            split2(x[0], x[1], xh, xl);
            split2(y[0], y[1], yh, yl);
            sts64(sb + OFF_W + (j * 4 + w) * 256 + (t >> 1) * 128 + (g & 1) * 64 + (g >> 1) * 16 + (t & 1) * 8,
                  (g & 1) ? xl : xh, (g & 1) ? yl : yh);
            __syncwarp();
            if (lane == 0) mbar_arrive(bars + (B_W + j) * 8);
        }
    } else {
        if (elect()) {
            asm volatile("prefetch.tensormap [%0];" :: "l"(&emap) : "memory");
            asm volatile("prefetch.tensormap [%0];" :: "l"(&fmap) : "memory");
            asm volatile("prefetch.tensormap [%0];" :: "l"(&vmap) : "memory");
            mbar_arm(bars + B_E * 8, 4 * TILE_B + HPC * ROWB);
            mbar_arm(bars + B_F * 8, 4 * TILE_B);
            mbar_arm(bars + (B_FULL + 31) * 8, STAGE_B);
#pragma unroll
            for (int j = 0; j < 3; j++) mbar_init(bars + (B_O + j) * 8, NV);
        }
        __syncthreads();
#pragma unroll 1
        for (int j = 0; j < HPC; j++) {
            mbar_wait(bars + (B_S + j) * 8);
            const float2 p0 = lds64f(sb + OFF_S + (j * 4 + 0) * 256 + lane * 8);
            const float2 p1 = lds64f(sb + OFF_S + (j * 4 + 1) * 256 + lane * 8);
            const float2 p2 = lds64f(sb + OFF_S + (j * 4 + 2) * 256 + lane * 8);
            const float2 p3 = lds64f(sb + OFF_S + (j * 4 + 3) * 256 + lane * 8);
            red_add4(entry16(2, j), (p0.x + p1.x) + (p2.x + p3.x), (p0.y + p1.y) + (p2.y + p3.y), 1.f, 0.f);
        }
#pragma unroll 1
        for (int j = 0; j < HPC - 1; j++) {
            mbar_wait(bars + (B_P + j + 1) * 8);
            mbar_wait(bars + (B_O + j) * 8);
            __nv_bfloat16* op = out + (j * NG + grp) * DH + lane;
            float o[2][3];
            float4 r[2];
#pragma unroll
            for (int i = 0; i < 2; i++) {
#pragma unroll
                for (int x = 0; x < 3; x++) o[i][x] = __uint_as_float(lds32(sb + OFF_O + (j * DH + (i * 3 + x) * 32 + lane) * 4));
                r[i] = atom_add4(entry16(1, 2 * j + i), o[i][0], o[i][1], o[i][2], 1.f);
            }
#pragma unroll
            for (int i = 0; i < 2; i++)
                if (r[i].w == (float)(NC - 1)) {
                    op[i * 96] = __float2bfloat16(r[i].x + o[i][0]);
                    op[i * 96 + 32] = __float2bfloat16(r[i].y + o[i][1]);
                    op[i * 96 + 64] = __float2bfloat16(r[i].z + o[i][2]);
                    clear16(entry16(1, 2 * j + i));
                    if (i == 1 || j == 0) clear16(entry16(2, j + i));
                }
        }
    }
}

static CUtensorMap make_map(const void* p, uint64_t inner, uint64_t rows, uint32_t box_rows) {
    typedef CUresult (*EncodeFn)(CUtensorMap*, CUtensorMapDataType, cuuint32_t, void*, const cuuint64_t*, const cuuint64_t*,
                                 const cuuint32_t*, const cuuint32_t*, CUtensorMapInterleave, CUtensorMapSwizzle,
                                 CUtensorMapL2promotion, CUtensorMapFloatOOBfill);
    void* fn = nullptr;
    cudaDriverEntryPointQueryResult qr;
    cudaGetDriverEntryPoint("cuTensorMapEncodeTiled", &fn, cudaEnableDefault, &qr);
    CUtensorMap m;
    const cuuint64_t dims[2] = {inner, rows};
    const cuuint64_t strides[1] = {inner * 2};
    const cuuint32_t box[2] = {64, box_rows};
    const cuuint32_t estr[2] = {1, 1};
    ((EncodeFn)fn)(&m, CU_TENSOR_MAP_DATA_TYPE_BFLOAT16, 2, (void*)p, dims, strides, box, estr, CU_TENSOR_MAP_INTERLEAVE_NONE,
                   CU_TENSOR_MAP_SWIZZLE_128B, CU_TENSOR_MAP_L2_PROMOTION_NONE, CU_TENSOR_MAP_FLOAT_OOB_FILL_NONE);
    return m;
}

}

extern "C" void kernel_launch(void* const* d_in, const int* in_sizes, int n_in, void* d_out, int out_size) {
    using namespace lf;
    void* acc = nullptr;
    cudaGetSymbolAddress(&acc, g_acc);
    acc = (void*)(((uintptr_t)acc + ACC_GROUP - 1) & ~(uintptr_t)(ACC_GROUP - 1));
    cudaFuncSetAttribute(linformer_decode_kernel, cudaFuncAttributeMaxDynamicSharedMemorySize, SMEM_BYTES);
    cudaLaunchAttribute attr;
    attr.id = cudaLaunchAttributeCooperative;
    attr.val.cooperative = 1;
    cudaLaunchConfig_t cfg = {};
    cfg.gridDim = dim3(NCTA);
    cfg.blockDim = dim3(NWARPS * 32);
    cfg.dynamicSmemBytes = SMEM_BYTES;
    cfg.stream = cudaStreamPerThread;
    cfg.attrs = &attr;
    cfg.numAttrs = 1;
    cudaLaunchKernelEx(&cfg, linformer_decode_kernel,
                       (const __nv_bfloat16*)d_in[1], (const __nv_bfloat16*)d_in[0], (__nv_bfloat16*)d_out, (unsigned char*)acc,
                       make_map(d_in[2], 64, (uint64_t)H * SKV * 3, 192),
                       make_map(d_in[3], SKV, 64, 64), make_map(d_in[4], SKV, 64, 64));
}
```

```cpp
#include <cuda.h>
#include <cuda_runtime.h>
#include <cuda_bf16.h>
#include <stdint.h>

namespace lf {

constexpr int H = 32, SKV = 4096, DH = 192;
constexpr int NCTA = 128;
constexpr int NC = 16;
constexpr int NG = 8;
constexpr int HPC = 4;
constexpr int ROWB = DH * 2;
constexpr int STAGE_B = 64 * ROWB;
constexpr int NS = 8;
constexpr int NSTAGE = 32;
constexpr int FLY_START = 3;
constexpr int FLY_MIN = 2;
constexpr int FLY_MAX = 5;
constexpr int LEAD_NS = 180;
constexpr int READ_AT = 10;
constexpr int NV = 6;
constexpr int NWARPS = 1 + NV + 4 + 1;

constexpr int TILE_B = 64 * 128;
constexpr int OFF_X = NS * STAGE_B;
constexpr int OFF_W = OFF_X + 2 * TILE_B;
constexpr int OFF_P = OFF_W + 4096;
constexpr int OFF_S = OFF_P + 1024;
constexpr int OFF_Q = OFF_S + 4096;
constexpr int OFF_O = OFF_Q + 1536;
constexpr int OFF_BAR = OFF_O + 2304;
constexpr int B_FULL = 0, B_FREE = 33 - 6, B_S = 59, B_P = 63, B_W = 67, B_O = 71, B_E = 74, B_F = 75, NBAR = 76;
constexpr int SMEM_BYTES = OFF_BAR + NBAR * 8;

constexpr int SPIN_LIMIT = 1 << 20;

constexpr int ACC_GROUP = 65536;
__device__ unsigned char g_acc[(NG + 1) * ACC_GROUP];
__device__ __forceinline__ int acc_line(int set, int i) {
    return set * 4096 + (i & 1) * 256 + ((i >> 1) & 3) * 1024 + (i >> 3) * 16384;
}

__device__ __forceinline__ uint32_t smem_u32(const void* p) { return (uint32_t)__cvta_generic_to_shared(p); }
__device__ __forceinline__ void mbar_init(uint32_t bar, uint32_t cnt) {
    asm volatile("mbarrier.init.shared::cta.b64 [%0], %1;" :: "r"(bar), "r"(cnt) : "memory");
}
__device__ __forceinline__ void mbar_arm(uint32_t bar, uint32_t bytes) {
    mbar_init(bar, 1);
    asm volatile("mbarrier.arrive.expect_tx.shared::cta.b64 _, [%0], %1;" :: "r"(bar), "r"(bytes) : "memory");
}
__device__ __forceinline__ void mbar_arrive(uint32_t bar, uint32_t n = 1) {
    asm volatile("mbarrier.arrive.shared::cta.b64 _, [%0], %1;" :: "r"(bar), "r"(n) : "memory");
}
__device__ __forceinline__ bool mbar_test(uint32_t bar) {
    uint32_t ok;
    asm volatile("{\n.reg .pred p;\nmbarrier.test_wait.parity.shared::cta.b64 p, [%1], 0;\nselp.u32 %0, 1, 0, p;\n}"
                 : "=r"(ok) : "r"(bar) : "memory");
    return ok;
}
__device__ __forceinline__ void mbar_wait(uint32_t bar) {
    asm volatile("{\n.reg .pred p, q;\n.reg .u32 n;\nmov.u32 n, 0;\n"
                 "LF_WAIT_%=:\n"
                 "mbarrier.try_wait.parity.shared::cta.b64 p, [%0], 0;\n"
                 "add.u32 n, n, 1;\n"
                 "setp.lt.u32 q, n, %1;\n"
                 "and.pred q, q, !p;\n"
                 "@q bra LF_WAIT_%=;\n}"
                 :: "r"(bar), "n"(SPIN_LIMIT) : "memory");
}
constexpr uint64_t EVICT_FIRST = 0x12F0000000000000ull;
__device__ __forceinline__ void bulk_g2s(uint32_t dst, const void* src, uint32_t bytes, uint32_t bar) {
    asm volatile("cp.async.bulk.shared::cluster.global.mbarrier::complete_tx::bytes.L2::cache_hint [%0], [%1], %2, [%3], %4;"
                 :: "r"(dst), "l"(src), "r"(bytes), "r"(bar), "l"(EVICT_FIRST) : "memory");
}
__device__ __forceinline__ void tile_g2s(uint32_t dst, const CUtensorMap* map, int n0, uint32_t bar) {
    asm volatile("cp.async.bulk.tensor.2d.shared::cluster.global.mbarrier::complete_tx::bytes [%0], [%1, {%2, %3}], [%4];"
                 :: "r"(dst), "l"(map), "r"(n0), "r"(0), "r"(bar) : "memory");
}
__device__ __forceinline__ void lines_g2s(uint32_t dst, const CUtensorMap* map, int line0, uint32_t bar) {
    asm volatile("cp.async.bulk.tensor.2d.shared::cluster.global.mbarrier::complete_tx::bytes.L2::cache_hint [%0], [%1, {%2, %3}], [%4], %5;"
                 :: "r"(dst), "l"(map), "r"(0), "r"(line0), "r"(bar), "l"(EVICT_FIRST) : "memory");
}
__device__ __forceinline__ uint32_t now_ns() {
    uint32_t t;
    asm volatile("mov.u32 %0, %globaltimer_lo;" : "=r"(t));
    return t;
}
__device__ __forceinline__ bool elect() {
    uint32_t p;
    asm volatile("{\n.reg .pred P;\nelect.sync _|P, 0xffffffff;\nselp.u32 %0, 1, 0, P;\n}" : "=r"(p));
    return p;
}
__device__ __forceinline__ void mma(float (&d)[4], uint32_t a0, uint32_t a1, uint32_t a2, uint32_t a3, uint32_t b0, uint32_t b1) {
    asm volatile("mma.sync.aligned.m16n8k16.row.col.f32.bf16.bf16.f32 {%0,%1,%2,%3}, {%4,%5,%6,%7}, {%8,%9}, {%0,%1,%2,%3};"
                 : "+f"(d[0]), "+f"(d[1]), "+f"(d[2]), "+f"(d[3])
                 : "r"(a0), "r"(a1), "r"(a2), "r"(a3), "r"(b0), "r"(b1));
}
template <int N>
__device__ __forceinline__ void zero(float (&d)[N][4]) {
#pragma unroll
    for (int i = 0; i < N; i++) d[i][0] = d[i][1] = d[i][2] = d[i][3] = 0.f;
}
__device__ __forceinline__ uint4 lds128(uint32_t addr) {
    uint4 v;
    asm volatile("ld.shared.v4.u32 {%0,%1,%2,%3}, [%4];" : "=r"(v.x), "=r"(v.y), "=r"(v.z), "=r"(v.w) : "r"(addr) : "memory");
    return v;
}
__device__ __forceinline__ float2 lds64f(uint32_t addr) {
    float2 v;
    asm volatile("ld.shared.v2.f32 {%0,%1}, [%2];" : "=f"(v.x), "=f"(v.y) : "r"(addr) : "memory");
    return v;
}
__device__ __forceinline__ uint32_t lds32(uint32_t addr) {
    uint32_t v;
    asm volatile("ld.shared.u32 %0, [%1];" : "=r"(v) : "r"(addr) : "memory");
    return v;
}
__device__ __forceinline__ void sts64(uint32_t addr, uint32_t x, uint32_t y) {
    asm volatile("st.shared.v2.u32 [%0], {%1,%2};" :: "r"(addr), "r"(x), "r"(y) : "memory");
}
__device__ __forceinline__ void sts32(uint32_t addr, float x) {
    asm volatile("st.shared.f32 [%0], %1;" :: "r"(addr), "f"(x) : "memory");
}
__device__ __forceinline__ uint4 ldsm4t(uint32_t addr) {
    uint4 v;
    asm volatile("ldmatrix.sync.aligned.m8n8.x4.trans.shared.b16 {%0,%1,%2,%3}, [%4];"
                 : "=r"(v.x), "=r"(v.y), "=r"(v.z), "=r"(v.w) : "r"(addr) : "memory");
    return v;
}
__device__ __forceinline__ float fsel(float a, float b, uint32_t pick_b) {
    float r;
    asm("{\n.reg .pred s;\nsetp.ne.u32 s, %3, 0;\nselp.f32 %0, %2, %1, s;\n}" : "=f"(r) : "f"(a), "f"(b), "r"(pick_b));
    return r;
}
__device__ __forceinline__ uint32_t pack_bf16(float x, float y) {
    uint32_t r;
    asm("cvt.rn.bf16x2.f32 %0, %1, %2;" : "=r"(r) : "f"(y), "f"(x));
    return r;
}
__device__ __forceinline__ void split2(float x, float y, uint32_t& hi, uint32_t& lo) {
    hi = pack_bf16(x, y);
    lo = pack_bf16(x - __uint_as_float(hi << 16), y - __uint_as_float(hi & 0xffff0000u));
}
__device__ __forceinline__ uint32_t word(const uint4& v, int i) { return i == 0 ? v.x : i == 1 ? v.y : i == 2 ? v.z : v.w; }

__device__ __forceinline__ float4 atom_add4(void* p, float x, float y, float z, float w) {
    float4 r;
    asm volatile("atom.relaxed.gpu.global.add.v4.f32 {%0,%1,%2,%3}, [%4], {%5,%6,%7,%8};"
                 : "=f"(r.x), "=f"(r.y), "=f"(r.z), "=f"(r.w) : "l"(p), "f"(x), "f"(y), "f"(z), "f"(w) : "memory");
    return r;
}
__device__ __forceinline__ void red_add4(void* p, float x, float y, float z, float w) {
    asm volatile("red.relaxed.gpu.global.add.v4.f32 [%0], {%1,%2,%3,%4};" :: "l"(p), "f"(x), "f"(y), "f"(z), "f"(w) : "memory");
}
__device__ __forceinline__ float4 ld_relaxed16(const void* p) {
    float4 r;
    asm volatile("{\n.reg .b128 u;\n.reg .b64 a, b;\nld.relaxed.gpu.global.b128 u, [%4];\nmov.b128 {a, b}, u;\n"
                 "mov.b64 {%0, %1}, a;\nmov.b64 {%2, %3}, b;\n}"
                 : "=f"(r.x), "=f"(r.y), "=f"(r.z), "=f"(r.w) : "l"(p) : "memory");
    return r;
}
__device__ __forceinline__ void clear16(void* p) {
    asm volatile("st.global.v4.u32 [%0], {%1,%1,%1,%1};" :: "l"(p), "r"(0) : "memory");
}

__global__ void __launch_bounds__(NWARPS * 32, 1)
linformer_decode_kernel(const __nv_bfloat16* __restrict__ k, const __nv_bfloat16* __restrict__ q,
                        __nv_bfloat16* __restrict__ out, unsigned char* __restrict__ acc_all, int period_ns,
                        const __grid_constant__ CUtensorMap vmap, const __grid_constant__ CUtensorMap emap,
                        const __grid_constant__ CUtensorMap fmap) {
    extern __shared__ __align__(1024) unsigned char smem[];
    const uint32_t sb = smem_u32(smem);
    const uint32_t bars = sb + OFF_BAR;
    const int grp = blockIdx.x & (NG - 1), c = blockIdx.x >> 3;

    {
        const uint32_t ofs = (grp * SKV + c * 64) * ROWB + (threadIdx.x >> 5) * (STAGE_B / NWARPS);
        if (elect()) asm volatile("cp.async.bulk.prefetch.L2.global [%0], %1;" :: "l"((const char*)k + ofs), "r"(STAGE_B / NWARPS) : "memory");
    }
    if (threadIdx.x < 32) {
        const bool leader = elect();
        const int row0 = grp * SKV + c * 64;
        auto issue_k = [&](int s) {
            const int row = row0 + (s >> 2) * NG * SKV + (s & 3) * 1024;
            bulk_g2s(sb + (s & (NS - 1)) * STAGE_B, (const char*)k + (size_t)row * ROWB, STAGE_B, bars + (B_FULL + s) * 8);
        };
        auto issue_v_half = [&](int s, int half, int bar) {
            const int row = row0 + ((s >> 2) & 3) * NG * SKV + (s & 3) * 1024 + half * 32;
            lines_g2s(sb + (s & (NS - 1)) * STAGE_B + half * (STAGE_B / 2), &vmap, row * 3, bars + (B_FULL + bar) * 8);
        };
        if (leader) {
            mbar_arm(bars + B_FULL * 8, STAGE_B);
            issue_k(0);
        }
        const uint32_t t0 = now_ns();
        __syncthreads();
        if (leader) {
#pragma unroll
            for (int j = 0; j < HPC; j++) bulk_g2s(sb + OFF_Q + j * ROWB, q + (j * NG + grp) * DH, ROWB, bars + B_E * 8);
#pragma unroll
            for (int w = 0; w < 4; w++)
                tile_g2s(sb + (w < 3 ? 6 * STAGE_B + w * TILE_B : OFF_X), &emap, w * 1024 + c * 64, bars + B_E * 8);
#pragma unroll
            for (int s = 1; s < FLY_START; s++) issue_k(s);
#pragma unroll
            for (int w = 0; w < 4; w++)
                tile_g2s(sb + (w < 3 ? 7 * STAGE_B + w * TILE_B : OFF_X + TILE_B), &fmap, w * 1024 + c * 64, bars + B_F * 8);

            uint32_t fly = (1u << FLY_START) - 1, scan = fly;
            uint32_t due = t0 + FLY_START * period_ns - LEAD_NS;
#pragma unroll 1
            for (int u = FLY_START, it = 0; u <= NSTAGE && it < SPIN_LIMIT * 64; it++) {
                const int limit = (int)(now_ns() - due) > 0 ? FLY_MAX : FLY_MIN;
                if (__popc(fly) < limit + (u == NSTAGE)) {
                    if (u >= 6 && u < NSTAGE) mbar_wait(bars + (B_FREE + u) * 8);
                    if (u < 16) {
                        issue_k(u);
                    } else {
                        if (u < NSTAGE) issue_v_half(u, 0, u);
                        if (u != NSTAGE - 1) issue_v_half(min(u, NSTAGE - 1), 1, u);
                    }
                    fly |= 1u << (u & 31);
                    due += u == NSTAGE - 1 ? period_ns / 2 : period_ns;
                    u++;
                } else {
                    if (!scan) scan = fly;
                    const int m = __ffs(scan) - 1;
                    scan &= scan - 1;
                    if (mbar_test(bars + (B_FULL + m) * 8)) fly ^= 1u << m;
                }
            }
        }
        return;
    }

    const int warp = __shfl_sync(0xffffffffu, threadIdx.x >> 5, 0), lane = threadIdx.x & 31;
    const int g = lane >> 2, t = lane & 3;
    unsigned char* const acc_g = acc_all + grp * ACC_GROUP;
    auto entry16 = [&](int set, int blk) { return acc_g + acc_line(set, 4 * blk + (lane >> 3)) + (lane & 7) * 16; };

    if (warp <= NV) {
        const int vw = warp - 1;
        if (elect()) {
#pragma unroll
            for (int i = 0; i < 5; i++) {
                const int s = vw * 5 + i;
                mbar_arm(bars + (B_FULL + 1 + s) * 8, STAGE_B);
                if (s < 26) mbar_init(bars + (B_FREE + 6 + s) * 8, NV);
            }
        }
        __syncthreads();

        if (vw < 4) {
            const int w = vw;
            const uint32_t tile = sb + (w < 3 ? 6 * STAGE_B + w * TILE_B : OFF_X);
            uint32_t ef[4][4][4];
            mbar_wait(bars + B_E * 8);
#pragma unroll
            for (int i = 0; i < 8; i++) {
                const uint4 ea = lds128(tile + (i * 8 + g) * 128 + (((2 * t) ^ g) << 4));
                const uint4 eb = lds128(tile + (i * 8 + g) * 128 + (((2 * t + 1) ^ g) << 4));
#pragma unroll
                for (int ks = 0; ks < 4; ks++) { ef[i >> 1][ks][i & 1] = word(ea, ks); ef[i >> 1][ks][2 + (i & 1)] = word(eb, ks); }
            }
            __syncwarp();
            if (lane == 0 && w < 3) mbar_arrive(bars + (B_FREE + 6) * 8, NV / 3);

            const uint32_t krow = sb + ((g & 3) * 16 + (g >> 2) * 8) * ROWB + t * 16;
            const uint32_t kofs0 = krow + (g & 1) * 64, kofs1 = krow + ((g & 1) ^ 1) * 64;
            const uint32_t qofs0 = sb + OFF_Q + t * 16 + (g & 1) * 4 + (g & 2) * 32, qofs1 = qofs0 ^ 64;
            const uint32_t m0 = (g == t) ? 0xffffffffu : 0u, m1 = (g == t + 4) ? 0xffffffffu : 0u;
#pragma unroll 1
            for (int j = 0; j < HPC; j++) {
                const int s = j * 4 + w;
                uint32_t qf[6][2];
#pragma unroll
                for (int i = 0; i < 6; i++) {
                    qf[i][0] = lds32(((i & 1) ? qofs1 : qofs0) + j * ROWB + (i >> 1) * 128);
                    qf[i][1] = lds32(((i & 1) ? qofs1 : qofs0) + j * ROWB + (i >> 1) * 128 + 8);
                }
                const uint32_t slot = (s & (NS - 1)) * STAGE_B;
                mbar_wait(bars + (B_FULL + s) * 8);
                float d[8][4];
                zero(d);
#pragma unroll
                for (int i = 0; i < 6; i++)
#pragma unroll
                    for (int u = 0; u < 8; u++) {
                        const uint4 kv = lds128(((i & 1) ? kofs1 : kofs0) + slot + u * ROWB + (i >> 1) * 128);
                        mma(d[u], kv.x, kv.y, kv.z, kv.w, qf[i][0], qf[i][1]);
                    }
                __syncwarp();
                if (lane == 0) mbar_arrive(bars + (B_FREE + s + NS) * 8, NV);

                float d2[4][4];
                zero(d2);
#pragma unroll
                for (int ks = 0; ks < 4; ks++) {
                    uint32_t hi, lo;
                    split2(d[2 * ks][0] + d[2 * ks][3], d[2 * ks + 1][0] + d[2 * ks + 1][3], hi, lo);
#pragma unroll
                    for (int i = 0; i < 4; i++) mma(d2[i], ef[i][ks][0], ef[i][ks][1], ef[i][ks][2], ef[i][ks][3], hi & m0, hi & m1);
#pragma unroll
                    for (int i = 0; i < 4; i++) mma(d2[i], ef[i][ks][0], ef[i][ks][1], ef[i][ks][2], ef[i][ks][3], lo & m0, lo & m1);
                }
                float x[4], y[4];
#pragma unroll
                for (int i = 0; i < 4; i++) { x[i] = d2[i][0] + d2[i][1]; y[i] = d2[i][2] + d2[i][3]; }
#pragma unroll
                for (int i = 0; i < 2; i++) {
                    x[i] = fsel(x[i], x[i + 2], t & 2) + __shfl_xor_sync(0xffffffffu, fsel(x[i + 2], x[i], t & 2), 2);
                    y[i] = fsel(y[i], y[i + 2], t & 2) + __shfl_xor_sync(0xffffffffu, fsel(y[i + 2], y[i], t & 2), 2);
                }
                const float sx = fsel(x[0], x[1], t & 1) + __shfl_xor_sync(0xffffffffu, fsel(x[1], x[0], t & 1), 1);
                const float sy = fsel(y[0], y[1], t & 1) + __shfl_xor_sync(0xffffffffu, fsel(y[1], y[0], t & 1), 1);
                sts32(sb + OFF_S + (j * 4 + w) * 256 + (16 * t + g) * 4, sx);
                sts32(sb + OFF_S + (j * 4 + w) * 256 + (16 * t + 8 + g) * 4, sy);
                __syncwarp();
                if (lane == 0) mbar_arrive(bars + (B_S + j) * 8);
            }
        }

        const int mat = lane >> 3, mi = lane & 7;
        uint32_t off[2];
#pragma unroll
        for (int u = 0; u < 2; u++) {
            const int cc = vw * 4 + u * 2 + (mat & 1), blk = cc >> 3;
            off[u] = sb + ((mat >> 1) * 8 + mi) * ROWB + blk * 128 + (((cc & 7) ^ ((3 * mi + blk) & 7)) << 4);
        }
        const uint32_t wofs = sb + OFF_W + (g & 1) * 64 + t * 16;
        const int col = vw * 32 + (t & 1) * 16 + (t >> 1) * 8 + g;
        unsigned char* accp = acc_g + acc_line(0, vw * 2 + (lane >> 4)) + (lane & 15) * 8;
        __nv_bfloat16* outp = out + (3 * NG + grp) * DH + col;
        asm volatile("" : "+l"(accp), "+l"(outp), "+r"(off[0]), "+r"(off[1]));

        auto v_head = [&](int j, bool release, bool last) {
            float acc[2][4];
            zero(acc);
            mbar_wait(bars + (B_W + j) * 8);
            uint4 wb[8];
#pragma unroll
            for (int i = 0; i < 8; i++) wb[i] = lds128(wofs + j * 1024 + i * 128);
            const uint32_t slot0 = (j & 1) * 4 * STAGE_B;
#pragma unroll
            for (int sub = 0; sub < 4; sub++) {
                const int s = 16 + j * 4 + sub;
                mbar_wait(bars + (B_FULL + s) * 8);
#pragma unroll
                for (int x = sub * 4; x < sub * 4 + 4; x++) {
                    if (last && x == 14) mbar_wait(bars + (B_FULL + NSTAGE) * 8);
#pragma unroll
                    for (int u = 0; u < 2; u++) {
                        const uint4 a = ldsm4t(off[u] + slot0 + x * 16 * ROWB);
                        mma(acc[u], a.x, a.y, a.z, a.w, word(wb[x >> 1], (x & 1) * 2), word(wb[x >> 1], (x & 1) * 2 + 1));
                    }
                }
                if (release) {
                    __syncwarp();
                    if (lane == 0) mbar_arrive(bars + (B_FREE + s + NS) * 8);
                }
            }
            return fsel(fsel(acc[0][0] + acc[0][1], acc[0][2] + acc[0][3], t & 2),
                        fsel(acc[1][0] + acc[1][1], acc[1][2] + acc[1][3], t & 2), t & 1);
        };
#pragma unroll 1
        for (int j = 0; j < HPC - 1; j++) {
            sts32(sb + OFF_O + (j * DH + col) * 4, v_head(j, j < 2, false));
            __syncwarp();
            if (lane == 0) mbar_arrive(bars + (B_O + j) * 8);
        }
        const float ov = v_head(HPC - 1, false, true);
        float tot, cnt;
        asm volatile("atom.relaxed.gpu.global.add.v2.f32 {%0, %1}, [%2], {%3, 0f3F800000};"
                     : "=f"(tot), "=f"(cnt) : "l"(accp), "f"(ov) : "memory");
        asm volatile("{\n.reg .pred p;\n.reg .b16 h;\n"
                     "cvt.rn.bf16.f32 h, %2;\n"
                     "setp.eq.f32 p, %3, %4;\n"
                     "@p st.global.b16 [%1], h;\n"
                     "@p st.global.v2.u32 [%0], {0, 0};\n}"
                     :: "l"(accp), "l"(outp), "f"(tot + ov), "f"(cnt), "f"((float)(NC - 1)) : "memory");
    } else if (warp <= NV + 4) {
        const int w = warp - (NV + 1);
        const uint32_t tile = sb + (w < 3 ? 7 * STAGE_B + w * TILE_B : OFF_X + TILE_B);
        if (elect()) {
            mbar_init(bars + (B_S + w) * 8, 4);
            mbar_init(bars + (B_P + w) * 8, 1);
            mbar_init(bars + (B_W + w) * 8, 4);
        }
        __syncthreads();
        uint4 fr[16];
        mbar_wait(bars + B_F * 8);
#pragma unroll
        for (int i = 0; i < 16; i++)
            fr[i] = lds128(tile + ((i >> 1) * 8 + 2 * t + (i & 1)) * 128 + ((g ^ (2 * t + (i & 1))) << 4));
        __syncwarp();
        if (lane == 0 && w < 3) mbar_arrive(bars + (B_FREE + 7) * 8, NV / 3);
        uint32_t fb[8][8];
#pragma unroll
        for (int i = 0; i < 8; i++)
#pragma unroll
            for (int x = 0; x < 8; x++)
                fb[i][x] = __byte_perm(word(fr[2 * x], i >> 1), word(fr[2 * x + 1], i >> 1), (i & 1) ? 0x7632 : 0x5410);

#pragma unroll 1
        for (int j = 0; j < HPC; j++) {
            if (j == w) {
                mbar_wait(bars + (B_FULL + READ_AT + 4 * j) * 8);
                float4 sc;
#pragma unroll 1
                for (int it = 0;; it++) {
                    sc = ld_relaxed16(entry16(2, j));
                    if (__all_sync(0xffffffffu, sc.z == (float)NC)) break;
                    if (it > SPIN_LIMIT) __trap();
                    __nanosleep(500);
                }
                const float scale = 0.07216878364870322f;
                sc.x *= scale; sc.y *= scale;
                float m = fmaxf(sc.x, sc.y);
#pragma unroll
                for (int o = 16; o > 0; o >>= 1) m = fmaxf(m, __shfl_xor_sync(0xffffffffu, m, o));
                const float e0 = expf(sc.x - m), e1 = expf(sc.y - m);
                float sum = e0 + e1;
#pragma unroll
                for (int o = 16; o > 0; o >>= 1) sum += __shfl_xor_sync(0xffffffffu, sum, o);
                uint32_t hi, lo;
                split2(e0 / sum, e1 / sum, hi, lo);
                sts64(sb + OFF_P + j * 256 + (g >> 1) * 64 + t * 16 + (g & 1) * 8, hi, lo);
                __syncwarp();
                if (lane == 0) mbar_arrive(bars + (B_P + j) * 8);
            }
            mbar_wait(bars + (B_P + j) * 8);
            float d[8][4];
            zero(d);
#pragma unroll
            for (int ks = 0; ks < 4; ks++) {
                const uint4 a = lds128(sb + OFF_P + j * 256 + ks * 64 + t * 16);
#pragma unroll
                for (int i = 0; i < 8; i++) mma(d[i], a.x, a.y, a.z, a.w, fb[i][2 * ks], fb[i][2 * ks + 1]);
            }
            float x[8], y[8];
#pragma unroll
            for (int i = 0; i < 8; i++) { x[i] = d[i][0] + d[i][2]; y[i] = d[i][1] + d[i][3]; }
#pragma unroll
            for (int i = 0; i < 4; i++) { x[i] = fsel(x[i], x[i + 4], g & 4); y[i] = fsel(y[i], y[i + 4], g & 4); }
#pragma unroll
            for (int i = 0; i < 2; i++) { x[i] = fsel(x[i], x[i + 2], g & 2); y[i] = fsel(y[i], y[i + 2], g & 2); }
            uint32_t xh, xl, yh, yl;
            split2(x[0], x[1], xh, xl);
            split2(y[0], y[1], yh, yl);
            sts64(sb + OFF_W + (j * 4 + w) * 256 + (t >> 1) * 128 + (g & 1) * 64 + (g >> 1) * 16 + (t & 1) * 8,
                  (g & 1) ? xl : xh, (g & 1) ? yl : yh);
            __syncwarp();
            if (lane == 0) mbar_arrive(bars + (B_W + j) * 8);
        }
    } else {
        if (elect()) {
            asm volatile("prefetch.tensormap [%0];" :: "l"(&emap) : "memory");
            asm volatile("prefetch.tensormap [%0];" :: "l"(&fmap) : "memory");
            asm volatile("prefetch.tensormap [%0];" :: "l"(&vmap) : "memory");
            mbar_arm(bars + B_E * 8, 4 * TILE_B + HPC * ROWB);
            mbar_arm(bars + B_F * 8, 4 * TILE_B);
            mbar_arm(bars + (B_FULL + 31) * 8, STAGE_B / 2);
            mbar_arm(bars + (B_FULL + 32) * 8, STAGE_B / 2);
#pragma unroll
            for (int j = 0; j < 3; j++) mbar_init(bars + (B_O + j) * 8, NV);
        }
        __syncthreads();
#pragma unroll 1
        for (int j = 0; j < HPC; j++) {
            mbar_wait(bars + (B_S + j) * 8);
            const float2 p0 = lds64f(sb + OFF_S + (j * 4 + 0) * 256 + lane * 8);
            const float2 p1 = lds64f(sb + OFF_S + (j * 4 + 1) * 256 + lane * 8);
            const float2 p2 = lds64f(sb + OFF_S + (j * 4 + 2) * 256 + lane * 8);
            const float2 p3 = lds64f(sb + OFF_S + (j * 4 + 3) * 256 + lane * 8);
            red_add4(entry16(2, j), (p0.x + p1.x) + (p2.x + p3.x), (p0.y + p1.y) + (p2.y + p3.y), 1.f, 0.f);
        }
#pragma unroll 1
        for (int j = 0; j < HPC - 1; j++) {
            mbar_wait(bars + (B_P + j + 1) * 8);
            mbar_wait(bars + (B_O + j) * 8);
            __nv_bfloat16* op = out + (j * NG + grp) * DH + lane;
            float o[2][3];
            float4 r[2];
#pragma unroll
            for (int i = 0; i < 2; i++) {
#pragma unroll
                for (int x = 0; x < 3; x++) o[i][x] = __uint_as_float(lds32(sb + OFF_O + (j * DH + (i * 3 + x) * 32 + lane) * 4));
                r[i] = atom_add4(entry16(1, 2 * j + i), o[i][0], o[i][1], o[i][2], 1.f);
            }
#pragma unroll
            for (int i = 0; i < 2; i++)
                if (r[i].w == (float)(NC - 1)) {
                    op[i * 96] = __float2bfloat16(r[i].x + o[i][0]);
                    op[i * 96 + 32] = __float2bfloat16(r[i].y + o[i][1]);
                    op[i * 96 + 64] = __float2bfloat16(r[i].z + o[i][2]);
                    clear16(entry16(1, 2 * j + i));
                    if (i == 1 || j == 0) clear16(entry16(2, j + i));
                }
        }
    }
}

static CUtensorMap make_map(const void* p, uint64_t inner, uint64_t rows, uint32_t box_rows) {
    typedef CUresult (*EncodeFn)(CUtensorMap*, CUtensorMapDataType, cuuint32_t, void*, const cuuint64_t*, const cuuint64_t*,
                                 const cuuint32_t*, const cuuint32_t*, CUtensorMapInterleave, CUtensorMapSwizzle,
                                 CUtensorMapL2promotion, CUtensorMapFloatOOBfill);
    void* fn = nullptr;
    cudaDriverEntryPointQueryResult qr;
    cudaGetDriverEntryPoint("cuTensorMapEncodeTiled", &fn, cudaEnableDefault, &qr);
    CUtensorMap m;
    const cuuint64_t dims[2] = {inner, rows};
    const cuuint64_t strides[1] = {inner * 2};
    const cuuint32_t box[2] = {64, box_rows};
    const cuuint32_t estr[2] = {1, 1};
    ((EncodeFn)fn)(&m, CU_TENSOR_MAP_DATA_TYPE_BFLOAT16, 2, (void*)p, dims, strides, box, estr, CU_TENSOR_MAP_INTERLEAVE_NONE,
                   CU_TENSOR_MAP_SWIZZLE_128B, CU_TENSOR_MAP_L2_PROMOTION_NONE, CU_TENSOR_MAP_FLOAT_OOB_FILL_NONE);
    return m;
}

}

extern "C" void kernel_launch(void* const* d_in, const int* in_sizes, int n_in, void* d_out, int out_size) {
    using namespace lf;
    void* acc = nullptr;
    cudaGetSymbolAddress(&acc, g_acc);
    acc = (void*)(((uintptr_t)acc + ACC_GROUP - 1) & ~(uintptr_t)(ACC_GROUP - 1));
    cudaFuncSetAttribute(linformer_decode_kernel, cudaFuncAttributeMaxDynamicSharedMemorySize, SMEM_BYTES);
    int dev = 0, mem_khz = 0, bus_bits = 0;
    cudaGetDevice(&dev);
    cudaDeviceGetAttribute(&mem_khz, cudaDevAttrMemoryClockRate, dev);
    cudaDeviceGetAttribute(&bus_bits, cudaDevAttrGlobalMemoryBusWidth, dev);
    const int period_ns = (int)((double)NCTA * STAGE_B / (0.9775 * 2e-6 * mem_khz * (bus_bits / 8)));
    cudaLaunchAttribute attr;
    attr.id = cudaLaunchAttributeCooperative;
    attr.val.cooperative = 1;
    cudaLaunchConfig_t cfg = {};
    cfg.gridDim = dim3(NCTA);
    cfg.blockDim = dim3(NWARPS * 32);
    cfg.dynamicSmemBytes = SMEM_BYTES;
    cfg.stream = cudaStreamPerThread;
    cfg.attrs = &attr;
    cfg.numAttrs = 1;
    cudaLaunchKernelEx(&cfg, linformer_decode_kernel,
                       (const __nv_bfloat16*)d_in[1], (const __nv_bfloat16*)d_in[0], (__nv_bfloat16*)d_out, (unsigned char*)acc, period_ns,
                       make_map(d_in[2], 64, (uint64_t)H * SKV * 3, 96),
                       make_map(d_in[3], SKV, 64, 64), make_map(d_in[4], SKV, 64, 64));
}
```

```cpp
#include <cuda.h>
#include <cuda_runtime.h>
#include <cuda_bf16.h>
#include <stdint.h>

namespace lf {

constexpr int H = 32, SKV = 4096, DH = 192;
constexpr int NCTA = 128;
constexpr int NC = 16;
constexpr int NG = 8;
constexpr int HPC = 4;
constexpr int ROWB = DH * 2;
constexpr int STAGE_B = 64 * ROWB;
constexpr int NS = 6;
constexpr int NSTAGE = 32;
constexpr int NUNIT = NSTAGE + 4;
constexpr int TAIL_ROW = SKV - 512;
constexpr int SLICE_B = 96;
constexpr int TAIL_SLOT = NSTAGE % NS;
constexpr int NV = 6;
constexpr int NWARPS = 1 + NV + 4 + 1;

#define LF_LEAD 500
#define LF_TAIL_LAG 200
#define LF_POLL_LAG 400
constexpr int FLY_MIN = 2, FLY_MAX = 5;
constexpr int LEAD_NS = LF_LEAD;
constexpr int TAIL_LAG_NS = LF_TAIL_LAG;
constexpr int POLL_LAG_NS = LF_POLL_LAG;
constexpr int READ_AT = 8;

constexpr int TILE_B = 64 * 128;
constexpr int OFF_EF = 3 * STAGE_B + TILE_B;
constexpr int OFF_G = NS * STAGE_B;
constexpr int OFF_W = OFF_G + 8 * TILE_B;
constexpr int OFF_P = OFF_W + 6144;
constexpr int OFF_S = OFF_P + 1024;
constexpr int OFF_Q = OFF_S + 4096;
constexpr int OFF_T = OFF_Q + 1536;
constexpr int OFF_BAR = OFF_T + 192;
constexpr int B_FULL = 0, B_FREE = NUNIT - 3, B_S = 67, B_P = 71, B_W = 75, B_O = 80, B_T = 81, B_E = 82, B_F = 83, B_G = 84;
constexpr int SMEM_BYTES = OFF_BAR + 85 * 8;

constexpr int SPIN_LIMIT = 1 << 20;

constexpr int ACC_GROUP = 65536, ACC_SET = 4096;
__device__ unsigned char g_acc[(NG + 1) * ACC_GROUP];
__device__ __forceinline__ int acc_line(int i) { return (i & 1) * 256 + ((i >> 1) & 3) * 1024 + (i >> 3) * 16384; }

__device__ __forceinline__ uint32_t smem_u32(const void* p) { return (uint32_t)__cvta_generic_to_shared(p); }
__device__ __forceinline__ void mbar_init(uint32_t bar, uint32_t cnt) {
    asm volatile("mbarrier.init.shared::cta.b64 [%0], %1;" :: "r"(bar), "r"(cnt) : "memory");
}
__device__ __forceinline__ void mbar_arm(uint32_t bar, uint32_t bytes) {
    mbar_init(bar, 1);
    asm volatile("mbarrier.arrive.expect_tx.shared::cta.b64 _, [%0], %1;" :: "r"(bar), "r"(bytes) : "memory");
}
__device__ __forceinline__ void mbar_arrive(uint32_t bar, uint32_t n = 1) {
    asm volatile("mbarrier.arrive.shared::cta.b64 _, [%0], %1;" :: "r"(bar), "r"(n) : "memory");
}
__device__ __forceinline__ bool mbar_test(uint32_t bar) {
    uint32_t ok;
    asm volatile("{\n.reg .pred p;\nmbarrier.test_wait.parity.shared::cta.b64 p, [%1], 0;\nselp.u32 %0, 1, 0, p;\n}"
                 : "=r"(ok) : "r"(bar) : "memory");
    return ok;
}
__device__ __forceinline__ void mbar_wait(uint32_t bar) {
    asm volatile("{\n.reg .pred p, q;\n.reg .u32 n;\nmov.u32 n, 0;\n"
                 "LF_WAIT_%=:\n"
                 "mbarrier.try_wait.parity.shared::cta.b64 p, [%0], 0;\n"
                 "add.u32 n, n, 1;\n"
                 "setp.lt.u32 q, n, %1;\n"
                 "and.pred q, q, !p;\n"
                 "@q bra LF_WAIT_%=;\n}"
                 :: "r"(bar), "n"(SPIN_LIMIT) : "memory");
}
constexpr uint64_t EVICT_FIRST = 0x12F0000000000000ull;
__device__ __forceinline__ void bulk_g2s(uint32_t dst, const void* src, uint32_t bytes, uint32_t bar) {
    asm volatile("cp.async.bulk.shared::cluster.global.mbarrier::complete_tx::bytes.L2::cache_hint [%0], [%1], %2, [%3], %4;"
                 :: "r"(dst), "l"(src), "r"(bytes), "r"(bar), "l"(EVICT_FIRST) : "memory");
}
__device__ __forceinline__ void tile_g2s(uint32_t dst, const CUtensorMap* map, int x, int y, uint32_t bar) {
    asm volatile("cp.async.bulk.tensor.2d.shared::cluster.global.mbarrier::complete_tx::bytes [%0], [%1, {%2, %3}], [%4];"
                 :: "r"(dst), "l"(map), "r"(x), "r"(y), "r"(bar) : "memory");
}
__device__ __forceinline__ void lines_g2s(uint32_t dst, const CUtensorMap* map, int line0, uint32_t bar) {
    asm volatile("cp.async.bulk.tensor.2d.shared::cluster.global.mbarrier::complete_tx::bytes.L2::cache_hint [%0], [%1, {%2, %3}], [%4], %5;"
                 :: "r"(dst), "l"(map), "r"(0), "r"(line0), "r"(bar), "l"(EVICT_FIRST) : "memory");
}
__device__ __forceinline__ uint32_t now_ns() {
    uint32_t t;
    asm volatile("mov.u32 %0, %globaltimer_lo;" : "=r"(t));
    return t;
}
__device__ __forceinline__ bool elect() {
    uint32_t p;
    asm volatile("{\n.reg .pred P;\nelect.sync _|P, 0xffffffff;\nselp.u32 %0, 1, 0, P;\n}" : "=r"(p));
    return p;
}
__device__ __forceinline__ void mma(float (&d)[4], uint32_t a0, uint32_t a1, uint32_t a2, uint32_t a3, uint32_t b0, uint32_t b1) {
    asm volatile("mma.sync.aligned.m16n8k16.row.col.f32.bf16.bf16.f32 {%0,%1,%2,%3}, {%4,%5,%6,%7}, {%8,%9}, {%0,%1,%2,%3};"
                 : "+f"(d[0]), "+f"(d[1]), "+f"(d[2]), "+f"(d[3])
                 : "r"(a0), "r"(a1), "r"(a2), "r"(a3), "r"(b0), "r"(b1));
}
template <int N>
__device__ __forceinline__ void zero(float (&d)[N][4]) {
#pragma unroll
    for (int i = 0; i < N; i++) d[i][0] = d[i][1] = d[i][2] = d[i][3] = 0.f;
}
__device__ __forceinline__ uint4 lds128(uint32_t addr) {
    uint4 v;
    asm volatile("ld.shared.v4.u32 {%0,%1,%2,%3}, [%4];" : "=r"(v.x), "=r"(v.y), "=r"(v.z), "=r"(v.w) : "r"(addr) : "memory");
    return v;
}
__device__ __forceinline__ float2 lds64f(uint32_t addr) {
    float2 v;
    asm volatile("ld.shared.v2.f32 {%0,%1}, [%2];" : "=f"(v.x), "=f"(v.y) : "r"(addr) : "memory");
    return v;
}
__device__ __forceinline__ uint32_t lds32(uint32_t addr) {
    uint32_t v;
    asm volatile("ld.shared.u32 %0, [%1];" : "=r"(v) : "r"(addr) : "memory");
    return v;
}
__device__ __forceinline__ void sts64(uint32_t addr, uint32_t x, uint32_t y) {
    asm volatile("st.shared.v2.u32 [%0], {%1,%2};" :: "r"(addr), "r"(x), "r"(y) : "memory");
}
__device__ __forceinline__ void sts32(uint32_t addr, float x) {
    asm volatile("st.shared.f32 [%0], %1;" :: "r"(addr), "f"(x) : "memory");
}
__device__ __forceinline__ uint4 ldsm4t(uint32_t addr) {
    uint4 v;
    asm volatile("ldmatrix.sync.aligned.m8n8.x4.trans.shared.b16 {%0,%1,%2,%3}, [%4];"
                 : "=r"(v.x), "=r"(v.y), "=r"(v.z), "=r"(v.w) : "r"(addr) : "memory");
    return v;
}
__device__ __forceinline__ float fsel(float a, float b, uint32_t pick_b) {
    float r;
    asm("{\n.reg .pred s;\nsetp.ne.u32 s, %3, 0;\nselp.f32 %0, %2, %1, s;\n}" : "=f"(r) : "f"(a), "f"(b), "r"(pick_b));
    return r;
}
__device__ __forceinline__ uint32_t pack_bf16(float x, float y) {
    uint32_t r;
    asm("cvt.rn.bf16x2.f32 %0, %1, %2;" : "=r"(r) : "f"(y), "f"(x));
    return r;
}
__device__ __forceinline__ void split2(float x, float y, uint32_t& hi, uint32_t& lo) {
    hi = pack_bf16(x, y);
    lo = pack_bf16(x - __uint_as_float(hi << 16), y - __uint_as_float(hi & 0xffff0000u));
}
__device__ __forceinline__ uint32_t word(const uint4& v, int i) { return i == 0 ? v.x : i == 1 ? v.y : i == 2 ? v.z : v.w; }

__device__ __forceinline__ void red_add2(void* p, float x, float y) {
    asm volatile("red.relaxed.gpu.global.add.v2.f32 [%0], {%1,%2};" :: "l"(p), "f"(x), "f"(y) : "memory");
}
__device__ __forceinline__ void red_add4(void* p, float x, float y, float z, float w) {
    asm volatile("red.relaxed.gpu.global.add.v4.f32 [%0], {%1,%2,%3,%4};" :: "l"(p), "f"(x), "f"(y), "f"(z), "f"(w) : "memory");
}
__device__ __forceinline__ float4 ld_relaxed16(const void* p) {
    float4 r;
    asm volatile("{\n.reg .b128 u;\n.reg .b64 a, b;\nld.relaxed.gpu.global.b128 u, [%4];\nmov.b128 {a, b}, u;\n"
                 "mov.b64 {%0, %1}, a;\nmov.b64 {%2, %3}, b;\n}"
                 : "=f"(r.x), "=f"(r.y), "=f"(r.z), "=f"(r.w) : "l"(p) : "memory");
    return r;
}

__global__ void __launch_bounds__(NWARPS * 32, 1)
linformer_decode_kernel(const __nv_bfloat16* __restrict__ k, const __nv_bfloat16* __restrict__ q,
                        __nv_bfloat16* __restrict__ out, unsigned char* __restrict__ acc_all, int period_ns,
                        const __grid_constant__ CUtensorMap vmap, const __grid_constant__ CUtensorMap smap,
                        const __grid_constant__ CUtensorMap emap, const __grid_constant__ CUtensorMap fmap) {
    extern __shared__ __align__(1024) unsigned char smem[];
    const uint32_t sb = smem_u32(smem);
    const uint32_t bars = sb + OFF_BAR;
    const int grp = blockIdx.x & (NG - 1), c = blockIdx.x >> 3;

    {
        const uint32_t ofs = (grp * SKV + c * 64) * ROWB + (threadIdx.x >> 5) * (STAGE_B / NWARPS);
        if (elect()) asm volatile("cp.async.bulk.prefetch.L2.global [%0], %1;" :: "l"((const char*)k + ofs), "r"(STAGE_B / NWARPS) : "memory");
    }
    if (threadIdx.x < 32) {
        const bool leader = elect();
        auto issue_k = [&](int s, int slot) {
            const int row = (grp + (s >> 2) * NG) * SKV + (s & 3) * 1024 + c * 64;
            bulk_g2s(sb + slot * STAGE_B, (const char*)k + (size_t)row * ROWB, STAGE_B, bars + (B_FULL + s) * 8);
        };
        if (leader) {
            mbar_arm(bars + B_FULL * 8, STAGE_B);
            issue_k(0, 0);
        }
        const uint32_t t0 = now_ns();
        __syncthreads();
        if (leader) {
#pragma unroll
            for (int j = 0; j < HPC; j++) bulk_g2s(sb + OFF_Q + j * ROWB, q + (j * NG + grp) * DH, ROWB, bars + B_E * 8);
#pragma unroll
            for (int w = 0; w < 4; w++) tile_g2s(sb + OFF_EF + w * TILE_B, &emap, w * 1024 + c * 64, 0, bars + B_E * 8);
            issue_k(1, 1);
#pragma unroll
            for (int w = 0; w < 4; w++)
                tile_g2s(sb + OFF_EF + (4 + w) * TILE_B, &fmap, w * 1024 + c * (w < 3 ? 64 : 32), 0, bars + B_F * 8);
            issue_k(2, 2);
#pragma unroll 1
            for (int w = 0; w < 8; w++) tile_g2s(sb + OFF_G + w * TILE_B, &fmap, TAIL_ROW + w * 64, 0, bars + B_G * 8);

            uint32_t fly = 7, scan = fly;
            uint32_t due = t0 + 3 * period_ns - LEAD_NS;
#pragma unroll 1
            for (int u = 3, slot = 3, it = 0; u < NUNIT && it < SPIN_LIMIT * 64; it++) {
                const int limit = (int)(now_ns() - due) <= 0 ? FLY_MIN : u < NSTAGE ? FLY_MAX : NUNIT;
                if (__popc(fly) < limit) {
                    const uint32_t bar = bars + (B_FULL + u) * 8;
                    mbar_wait(bars + (B_FREE + (u < NSTAGE ? u : (NSTAGE + u) >> 1)) * 8);
                    if (u < 16) {
                        issue_k(u, slot);
                        due += period_ns;
                    } else if (u < NSTAGE) {
                        const bool full = (u & 3) != 3;
                        const int line = ((grp + ((u >> 2) & 3) * NG) * SKV + (u & 3) * 1024 + c * (full ? 64 : 32)) * 3;
                        lines_g2s(sb + slot * STAGE_B, &vmap, line, bar);
                        if (full) lines_g2s(sb + slot * STAGE_B + STAGE_B / 2, &vmap, line + 96, bar);
                        due += full ? period_ns : period_ns / 2;
                        if (u == NSTAGE - 1) due += TAIL_LAG_NS;
                    } else {
                        tile_g2s(sb + TAIL_SLOT * STAGE_B + (u - NSTAGE) * 128 * SLICE_B, &smap, (c & 3) * 48,
                                 (grp + (c >> 2) * NG) * SKV + TAIL_ROW + (u - NSTAGE) * 128, bar);
                        due += period_ns / 2;
                    }
                    fly |= 1u << (u & 31);
                    u++;
                    if (++slot == NS) slot = 0;
                } else {
                    if (!scan) scan = fly;
                    const int m = __ffs(scan) - 1;
                    scan &= scan - 1;
                    if (mbar_test(bars + (B_FULL + (u > NSTAGE && m < 4 ? NSTAGE + m : m)) * 8)) fly ^= 1u << m;
                }
            }
        }
        return;
    }

    const int warp = __shfl_sync(0xffffffffu, threadIdx.x >> 5, 0), lane = threadIdx.x & 31;
    const int g = lane >> 2, t = lane & 3;
    unsigned char* const acc_g = acc_all + grp * ACC_GROUP;
    unsigned char* const score_p = acc_g + acc_line(16 + (lane >> 3)) + (lane & 7) * 16;

    if (warp <= NV) {
        const int vw = warp - 1;
        if (elect()) {
#pragma unroll
            for (int i = 0; i < 5; i++) {
                const int u = vw * 5 + i + 1;
                mbar_arm(bars + (B_FULL + u) * 8, (u & 19) == 19 ? STAGE_B / 2 : STAGE_B);
                mbar_init(bars + (B_FREE + u + 2) * 8, NV);
            }
        }
        __syncthreads();

        if (vw < 4) {
            const int w = vw;
            const uint32_t tile = sb + OFF_EF + w * TILE_B;
            uint32_t ef[4][4][4];
            mbar_wait(bars + B_E * 8);
#pragma unroll
            for (int i = 0; i < 8; i++) {
                const uint4 ea = lds128(tile + (i * 8 + g) * 128 + (((2 * t) ^ g) << 4));
                const uint4 eb = lds128(tile + (i * 8 + g) * 128 + (((2 * t + 1) ^ g) << 4));
#pragma unroll
                for (int ks = 0; ks < 4; ks++) { ef[i >> 1][ks][i & 1] = word(ea, ks); ef[i >> 1][ks][2 + (i & 1)] = word(eb, ks); }
            }
            __syncwarp();
            if (lane == 0) mbar_arrive(bars + (B_FREE + (w < 2 ? 3 : 4)) * 8, w < 2 ? NV / 2 : NV / 3);

            const uint32_t kofs = sb + ((g & 3) * 16 + (g >> 2) * 8) * ROWB + t * 16 + (g & 1) * 64;
            const uint32_t qofs = sb + OFF_Q + t * 16 + (g & 1) * 4 + (g & 2) * 32;
            const uint32_t m0 = (g == t) ? 0xffffffffu : 0u, m1 = (g == t + 4) ? 0xffffffffu : 0u;
#pragma unroll 1
            for (int j = 0; j < HPC; j++) {
                const int s = j * 4 + w;
                uint32_t ka = kofs + (s % NS) * STAGE_B, qa = qofs + j * ROWB;
                mbar_wait(bars + (B_FULL + s) * 8);
                float d[8][4];
                zero(d);
#pragma unroll 1
                for (int i = 0; i < 3; i++, ka += 128, qa += 128) {
#pragma unroll
                    for (int h = 0; h < 2; h++) {
                        const uint32_t q0 = lds32(qa ^ (h * 64)), q1 = lds32((qa ^ (h * 64)) + 8);
#pragma unroll
                        for (int u = 0; u < 8; u++) {
                            const uint4 kv = lds128((ka ^ (h * 64)) + u * ROWB);
                            mma(d[u], kv.x, kv.y, kv.z, kv.w, q0, q1);
                        }
                    }
                }
                __syncwarp();
                if (lane == 0) mbar_arrive(bars + (B_FREE + s + NS) * 8, NV);

                float d2[4][4];
                zero(d2);
#pragma unroll
                for (int ks = 0; ks < 4; ks++) {
                    uint32_t hi, lo;
                    split2(d[2 * ks][0] + d[2 * ks][3], d[2 * ks + 1][0] + d[2 * ks + 1][3], hi, lo);
#pragma unroll
                    for (int i = 0; i < 4; i++) mma(d2[i], ef[i][ks][0], ef[i][ks][1], ef[i][ks][2], ef[i][ks][3], hi & m0, hi & m1);
#pragma unroll
                    for (int i = 0; i < 4; i++) mma(d2[i], ef[i][ks][0], ef[i][ks][1], ef[i][ks][2], ef[i][ks][3], lo & m0, lo & m1);
                }
                float x[4], y[4];
#pragma unroll
                for (int i = 0; i < 4; i++) { x[i] = d2[i][0] + d2[i][1]; y[i] = d2[i][2] + d2[i][3]; }
#pragma unroll
                for (int i = 0; i < 2; i++) {
                    x[i] = fsel(x[i], x[i + 2], t & 2) + __shfl_xor_sync(0xffffffffu, fsel(x[i + 2], x[i], t & 2), 2);
                    y[i] = fsel(y[i], y[i + 2], t & 2) + __shfl_xor_sync(0xffffffffu, fsel(y[i + 2], y[i], t & 2), 2);
                }
                const float sx = fsel(x[0], x[1], t & 1) + __shfl_xor_sync(0xffffffffu, fsel(x[1], x[0], t & 1), 1);
                const float sy = fsel(y[0], y[1], t & 1) + __shfl_xor_sync(0xffffffffu, fsel(y[1], y[0], t & 1), 1);
                sts32(sb + OFF_S + (j * 4 + w) * 256 + (16 * t + g) * 4, sx);
                sts32(sb + OFF_S + (j * 4 + w) * 256 + (16 * t + 8 + g) * 4, sy);
                __syncwarp();
                if (lane == 0) mbar_arrive(bars + (B_S + j) * 8);
            }
        }

        const int mat = lane >> 3, mi = lane & 7;
        const uint32_t wofs = sb + OFF_W + (g & 1) * 64 + t * 16;
        {
            uint32_t off[2];
#pragma unroll
            for (int u = 0; u < 2; u++) {
                const int cc = vw * 4 + u * 2 + (mat & 1), blk = cc >> 3;
                off[u] = sb + ((mat >> 1) * 8 + mi) * ROWB + blk * 128 + (((cc & 7) ^ ((3 * mi + blk) & 7)) << 4);
            }
            const int col = vw * 32 + (t & 1) * 16 + (t >> 1) * 8 + g;
            unsigned char* accp = acc_g + acc_line(col >> 4) + (col & 15) * 8;
            float acc[2][4];
            auto rows32 = [&](uint32_t ofs, const uint4& wb) {
#pragma unroll
                for (int x = 0; x < 2; x++)
#pragma unroll
                    for (int u = 0; u < 2; u++) {
                        const uint4 a = ldsm4t(off[u] + ofs + x * 16 * ROWB);
                        mma(acc[u], a.x, a.y, a.z, a.w, word(wb, 2 * x), word(wb, 2 * x + 1));
                    }
            };
#pragma unroll 1
            for (int s = 16, slot = 16 % NS; s < NSTAGE; s++) {
                if ((s & 3) == 0) {
                    zero(acc);
                    mbar_wait(bars + (B_W - 4 + (s >> 2)) * 8);
                }
                const uint4 w0 = lds128(wofs + (s - 16) * 256), w1 = lds128(wofs + (s - 16) * 256 + 128);
                mbar_wait(bars + (B_FULL + s) * 8);
                if ((s & 3) != 3) {
                    rows32(slot * STAGE_B, w0);
                    rows32(slot * STAGE_B + STAGE_B / 2, w1);
                } else {
                    rows32(slot * STAGE_B, w0);
                    red_add2(accp, fsel(fsel(acc[0][0] + acc[0][1], acc[0][2] + acc[0][3], t & 2),
                                        fsel(acc[1][0] + acc[1][1], acc[1][2] + acc[1][3], t & 2), t & 1), 1.f);
                    accp += ACC_SET;
                }
                __syncwarp();
                if (lane == 0 && (s < 28 || s == NSTAGE - 1)) mbar_arrive(bars + (s < 28 ? B_FREE + s + NS : B_O) * 8);
                if (++slot == NS) slot = 0;
            }
        }

        if (vw < 3) {
            uint32_t fa = sb + TAIL_SLOT * STAGE_B + ((mat >> 1) * 8 + mi) * SLICE_B + (2 * vw + ((mat & 1) ^ (mi >> 2))) * 16;
            const int tcol = vw * 16 + (t & 1) * 8 + g;
            __nv_bfloat16* outp = out + (grp + (c >> 2) * NG) * DH + (c & 3) * 48 + tcol;
            asm volatile("" : "+l"(outp));
            float acc[2][4];
            zero(acc);
            auto unit = [&](int i) {
                uint4 wb[4];
#pragma unroll
                for (int x = 0; x < 4; x++) wb[x] = lds128(wofs + HPC * 1024 + i * 512 + x * 128);
                mbar_wait(bars + (B_FULL + NSTAGE + i) * 8);
#pragma unroll
                for (int x = 0; x < 8; x++) {
                    const uint4 a = ldsm4t(fa + x * 16 * SLICE_B);
                    const bool sw = t >= 2;
                    mma(acc[x & 1], sw ? a.y : a.x, sw ? a.x : a.y, sw ? a.w : a.z, sw ? a.z : a.w,
                        word(wb[x >> 1], (x & 1) * 2), word(wb[x >> 1], (x & 1) * 2 + 1));
                }
                fa += 128 * SLICE_B;
            };
            mbar_wait(bars + (B_W + HPC) * 8);
#pragma unroll 1
            for (int i = 0; i < 3; i++) unit(i);
            mbar_wait(bars + B_T * 8);
            const float tot = __uint_as_float(lds32(sb + OFF_T + tcol * 4));
            unit(3);
            const float o = (tot + fsel(acc[0][0] + acc[0][1], acc[0][2] + acc[0][3], t & 1)) +
                            fsel(acc[1][0] + acc[1][1], acc[1][2] + acc[1][3], t & 1);
            asm volatile("{\n.reg .pred p;\n.reg .b16 h;\ncvt.rn.bf16.f32 h, %1;\nsetp.lt.u32 p, %2, 2;\n@p st.global.b16 [%0], h;\n}"
                         :: "l"(outp), "f"(o), "r"(t) : "memory");
        }
    } else if (warp <= NV + 4) {
        const int w = warp - (NV + 1);
        if (elect()) {
            mbar_init(bars + (B_S + w) * 8, 4);
            mbar_init(bars + (B_P + w) * 8, 1);
            mbar_init(bars + (B_W + w) * 8, 4);
            mbar_arm(bars + (B_FULL + NSTAGE + w) * 8, 128 * SLICE_B);
        }
        __syncthreads();
        uint32_t fb[8][8];
#pragma unroll 1
        for (int j = 0; j < HPC + 2; j++) {
            if (j == 0 || j >= HPC) {
                const uint32_t tile = sb + (j == 0 ? OFF_EF + 4 * TILE_B : OFF_G + (j - HPC) * 4 * TILE_B) + w * TILE_B;
                mbar_wait(bars + (j == 0 ? B_F : B_G) * 8);
#pragma unroll
                for (int x = 0; x < 8; x++) {
                    const uint4 f0 = lds128(tile + (x * 8 + 2 * t) * 128 + ((g ^ (2 * t)) << 4));
                    const uint4 f1 = lds128(tile + (x * 8 + 2 * t + 1) * 128 + ((g ^ (2 * t + 1)) << 4));
#pragma unroll
                    for (int i = 0; i < 8; i++) fb[i][x] = __byte_perm(word(f0, i >> 1), word(f1, i >> 1), (i & 1) ? 0x7632 : 0x5410);
                }
                __syncwarp();
                if (j == 0 && lane == 0) mbar_arrive(bars + (B_FREE + (w == 0 ? 4 : 5)) * 8, NV / 3);
            }
            if (j == w) {
                mbar_wait(bars + (B_FULL + READ_AT + 4 * j) * 8);
                float4 sc;
#pragma unroll 1
                for (int it = 0;; it++) {
                    sc = ld_relaxed16(score_p + j * ACC_SET);
                    if (__all_sync(0xffffffffu, sc.z == (float)NC)) break;
                    if (it > SPIN_LIMIT) __trap();
                    __nanosleep(500);
                }
                const float scale = 0.07216878364870322f;
                sc.x *= scale; sc.y *= scale;
                float m = fmaxf(sc.x, sc.y);
#pragma unroll
                for (int o = 16; o > 0; o >>= 1) m = fmaxf(m, __shfl_xor_sync(0xffffffffu, m, o));
                const float e0 = expf(sc.x - m), e1 = expf(sc.y - m);
                float sum = e0 + e1;
#pragma unroll
                for (int o = 16; o > 0; o >>= 1) sum += __shfl_xor_sync(0xffffffffu, sum, o);
                const float inv = 1.0f / sum;
                uint32_t hi, lo;
                split2(e0 * inv, e1 * inv, hi, lo);
                sts64(sb + OFF_P + j * 256 + (g >> 1) * 64 + t * 16 + (g & 1) * 8, hi, lo);
                __syncwarp();
                if (lane == 0) mbar_arrive(bars + (B_P + j) * 8);
            }
            const int pj = j < HPC ? j : c >> 2;
            mbar_wait(bars + (B_P + pj) * 8);
            float d[8][4];
            zero(d);
#pragma unroll
            for (int ks = 0; ks < 4; ks++) {
                const uint4 a = lds128(sb + OFF_P + pj * 256 + ks * 64 + t * 16);
#pragma unroll
                for (int i = 0; i < 8; i++) mma(d[i], a.x, a.y, a.z, a.w, fb[i][2 * ks], fb[i][2 * ks + 1]);
            }
            float x[8], y[8];
#pragma unroll
            for (int i = 0; i < 8; i++) { x[i] = d[i][0] + d[i][2]; y[i] = d[i][1] + d[i][3]; }
#pragma unroll
            for (int i = 0; i < 4; i++) { x[i] = fsel(x[i], x[i + 4], g & 4); y[i] = fsel(y[i], y[i + 4], g & 4); }
#pragma unroll
            for (int i = 0; i < 2; i++) { x[i] = fsel(x[i], x[i + 2], g & 2); y[i] = fsel(y[i], y[i + 2], g & 2); }
            uint32_t xh, xl, yh, yl;
            split2(x[0], x[1], xh, xl);
            split2(y[0], y[1], yh, yl);
            sts64(sb + OFF_W + (j * 4 + w) * 256 + (t >> 1) * 128 + (g & 1) * 64 + (g >> 1) * 16 + (t & 1) * 8,
                  (g & 1) ? xl : xh, (g & 1) ? yl : yh);
            __syncwarp();
            if (lane == 0) mbar_arrive(bars + (B_W + min(j, HPC)) * 8);
        }
    } else {
        if (elect()) {
            asm volatile("prefetch.tensormap [%0];" :: "l"(&emap) : "memory");
            asm volatile("prefetch.tensormap [%0];" :: "l"(&fmap) : "memory");
            asm volatile("prefetch.tensormap [%0];" :: "l"(&vmap) : "memory");
            asm volatile("prefetch.tensormap [%0];" :: "l"(&smap) : "memory");
            mbar_arm(bars + B_E * 8, 4 * TILE_B + HPC * ROWB);
            mbar_arm(bars + B_F * 8, 4 * TILE_B);
            mbar_arm(bars + B_G * 8, 8 * TILE_B);
            mbar_arm(bars + (B_FULL + NSTAGE - 1) * 8, STAGE_B / 2);
            mbar_init(bars + (B_FREE + NSTAGE + 1) * 8, NV);
            mbar_init(bars + (B_W + HPC) * 8, 8);
            mbar_init(bars + B_O * 8, NV);
            mbar_init(bars + B_T * 8, 1);
        }
        __syncthreads();
#pragma unroll 1
        for (int j = 0; j < HPC; j++) {
            mbar_wait(bars + (B_S + j) * 8);
            const float2 p0 = lds64f(sb + OFF_S + (j * 4 + 0) * 256 + lane * 8);
            const float2 p1 = lds64f(sb + OFF_S + (j * 4 + 1) * 256 + lane * 8);
            const float2 p2 = lds64f(sb + OFF_S + (j * 4 + 2) * 256 + lane * 8);
            const float2 p3 = lds64f(sb + OFF_S + (j * 4 + 3) * 256 + lane * 8);
            red_add4(score_p + j * ACC_SET, (p0.x + p1.x) + (p2.x + p3.x), (p0.y + p1.y) + (p2.y + p3.y), 1.f, 0.f);
        }
        unsigned char* tp = acc_g + (c >> 2) * ACC_SET + acc_line(lane < 24 ? (c & 3) * 3 + (lane >> 3) : 16 + (c & 3)) + (lane & 7) * 16;
        mbar_wait(bars + (c < 12 ? B_FULL + 30 : B_O) * 8);
        for (const uint32_t t1 = now_ns(); now_ns() - t1 < POLL_LAG_NS;) {}
        float4 r;
#pragma unroll 1
        for (int it = 0;; it++) {
            if (lane < 24) r = ld_relaxed16(tp);
            if (__all_sync(0xffffffffu, lane >= 24 || (r.y == (float)NC && r.w == (float)NC))) break;
            if (it > SPIN_LIMIT) __trap();
        }
        if (lane < 24) sts64(sb + OFF_T + lane * 8, __float_as_uint(r.x), __float_as_uint(r.z));
        __syncwarp();
        if (lane == 0) mbar_arrive(bars + B_T * 8);
        asm volatile("st.global.v4.u32 [%0], {%1,%1,%1,%1};" :: "l"(tp), "r"(0) : "memory");
    }
}

static CUtensorMap make_map(const void* p, uint64_t cols, uint64_t rows, uint32_t box_cols, uint32_t box_rows) {
    typedef CUresult (*EncodeFn)(CUtensorMap*, CUtensorMapDataType, cuuint32_t, void*, const cuuint64_t*, const cuuint64_t*,
                                 const cuuint32_t*, const cuuint32_t*, CUtensorMapInterleave, CUtensorMapSwizzle,
                                 CUtensorMapL2promotion, CUtensorMapFloatOOBfill);
    void* fn = nullptr;
    cudaDriverEntryPointQueryResult qr;
    cudaGetDriverEntryPoint("cuTensorMapEncodeTiled", &fn, cudaEnableDefault, &qr);
    CUtensorMap m;
    const cuuint64_t dims[2] = {cols, rows};
    const cuuint64_t strides[1] = {cols * 2};
    const cuuint32_t box[2] = {box_cols, box_rows};
    const cuuint32_t estr[2] = {1, 1};
    ((EncodeFn)fn)(&m, CU_TENSOR_MAP_DATA_TYPE_BFLOAT16, 2, (void*)p, dims, strides, box, estr, CU_TENSOR_MAP_INTERLEAVE_NONE,
                   box_cols == 64 ? CU_TENSOR_MAP_SWIZZLE_128B : CU_TENSOR_MAP_SWIZZLE_NONE,
                   box_cols == 64 ? CU_TENSOR_MAP_L2_PROMOTION_NONE : CU_TENSOR_MAP_L2_PROMOTION_L2_128B,
                   CU_TENSOR_MAP_FLOAT_OOB_FILL_NONE);
    return m;
}

}

extern "C" void kernel_launch(void* const* d_in, const int* in_sizes, int n_in, void* d_out, int out_size) {
    using namespace lf;
    void* acc = nullptr;
    cudaGetSymbolAddress(&acc, g_acc);
    acc = (void*)(((uintptr_t)acc + ACC_GROUP - 1) & ~(uintptr_t)(ACC_GROUP - 1));
    cudaFuncSetAttribute(linformer_decode_kernel, cudaFuncAttributeMaxDynamicSharedMemorySize, SMEM_BYTES);
    int dev = 0, mem_khz = 0, bus_bits = 0;
    cudaGetDevice(&dev);
    cudaDeviceGetAttribute(&mem_khz, cudaDevAttrMemoryClockRate, dev);
    cudaDeviceGetAttribute(&bus_bits, cudaDevAttrGlobalMemoryBusWidth, dev);
    const int period_ns = (int)((double)NCTA * STAGE_B / (0.9775 * 2e-6 * mem_khz * (bus_bits / 8)));
    cudaLaunchAttribute attr;
    attr.id = cudaLaunchAttributeCooperative;
    attr.val.cooperative = 1;
    cudaLaunchConfig_t cfg = {};
    cfg.gridDim = dim3(NCTA);
    cfg.blockDim = dim3(NWARPS * 32);
    cfg.dynamicSmemBytes = SMEM_BYTES;
    cfg.stream = cudaStreamPerThread;
    cfg.attrs = &attr;
    cfg.numAttrs = 1;
    cudaLaunchKernelEx(&cfg, linformer_decode_kernel,
                       (const __nv_bfloat16*)d_in[1], (const __nv_bfloat16*)d_in[0], (__nv_bfloat16*)d_out, (unsigned char*)acc, period_ns,
                       make_map(d_in[2], 64, (uint64_t)H * SKV * 3, 64, 96),
                       make_map(d_in[2], DH, (uint64_t)H * SKV, 48, 128),
                       make_map(d_in[3], SKV, 64, 64, 64), make_map(d_in[4], SKV, 64, 64, 64));
}
```

```cpp
#include <cuda.h>
#include <cuda_runtime.h>
#include <cuda_bf16.h>
#include <stdint.h>

namespace lf {

constexpr int H = 32, SKV = 4096, DH = 192;
constexpr int NCTA = 128;
constexpr int NC = 16;
constexpr int NG = 8;
constexpr int HPC = 4;
constexpr int ROWB = DH * 2;
constexpr int STAGE_B = 64 * ROWB;
constexpr int NS = 6;
constexpr int NSTAGE = 32;
constexpr int NUNIT = NSTAGE + 4;
constexpr int TAIL_ROW = SKV - 512;
constexpr int SLICE_B = 96;
constexpr int TAIL_SLOT = NSTAGE % NS;
constexpr int NV = 6;
constexpr int NWARPS = 1 + NV + 4 + 1;

constexpr int FLY_MIN = 2, FLY_MAX = 5;
constexpr int LEAD_NS = 450;
constexpr int TAIL_LAG_NS = 180;
constexpr int POLL_LAG_NS = 200;
constexpr int READ_AT = 8;

constexpr int TILE_B = 64 * 128;
constexpr int OFF_EF = 3 * STAGE_B + TILE_B;
constexpr int OFF_G = NS * STAGE_B;
constexpr int OFF_W = OFF_G + 8 * TILE_B;
constexpr int OFF_P = OFF_W + 6144;
constexpr int OFF_S = OFF_P + 1024;
constexpr int OFF_Q = OFF_S + 4096;
constexpr int OFF_T = OFF_Q + 1536;
constexpr int OFF_BAR = OFF_T + 192;
constexpr int B_FULL = 0, B_FREE = NUNIT - 3, B_S = 67, B_P = 71, B_W = 75, B_O = 80, B_T = 81, B_E = 82, B_F = 83, B_G = 84;
constexpr int SMEM_BYTES = OFF_BAR + 85 * 8;

constexpr int SPIN_LIMIT = 1 << 20;

constexpr int ACC_GROUP = 65536, ACC_SET = 4096;
__device__ unsigned char g_acc[(NG + 1) * ACC_GROUP];
__device__ __forceinline__ int acc_line(int i) { return (i & 1) * 256 + ((i >> 1) & 3) * 1024 + (i >> 3) * 16384; }

__device__ __forceinline__ uint32_t smem_u32(const void* p) { return (uint32_t)__cvta_generic_to_shared(p); }
__device__ __forceinline__ void mbar_init(uint32_t bar, uint32_t cnt) {
    asm volatile("mbarrier.init.shared::cta.b64 [%0], %1;" :: "r"(bar), "r"(cnt) : "memory");
}
__device__ __forceinline__ void mbar_arm(uint32_t bar, uint32_t bytes) {
    mbar_init(bar, 1);
    asm volatile("mbarrier.arrive.expect_tx.shared::cta.b64 _, [%0], %1;" :: "r"(bar), "r"(bytes) : "memory");
}
__device__ __forceinline__ void mbar_arrive(uint32_t bar, uint32_t n = 1) {
    asm volatile("mbarrier.arrive.shared::cta.b64 _, [%0], %1;" :: "r"(bar), "r"(n) : "memory");
}
__device__ __forceinline__ bool mbar_test(uint32_t bar) {
    uint32_t ok;
    asm volatile("{\n.reg .pred p;\nmbarrier.test_wait.parity.shared::cta.b64 p, [%1], 0;\nselp.u32 %0, 1, 0, p;\n}"
                 : "=r"(ok) : "r"(bar) : "memory");
    return ok;
}
__device__ __forceinline__ void mbar_wait(uint32_t bar) {
    asm volatile("{\n.reg .pred p, q;\n.reg .u32 n;\nmov.u32 n, 0;\n"
                 "LF_WAIT_%=:\n"
                 "mbarrier.try_wait.parity.shared::cta.b64 p, [%0], 0;\n"
                 "add.u32 n, n, 1;\n"
                 "setp.lt.u32 q, n, %1;\n"
                 "and.pred q, q, !p;\n"
                 "@q bra LF_WAIT_%=;\n}"
                 :: "r"(bar), "n"(SPIN_LIMIT) : "memory");
}
constexpr uint64_t EVICT_FIRST = 0x12F0000000000000ull;
__device__ __forceinline__ void bulk_g2s(uint32_t dst, const void* src, uint32_t bytes, uint32_t bar) {
    asm volatile("cp.async.bulk.shared::cluster.global.mbarrier::complete_tx::bytes.L2::cache_hint [%0], [%1], %2, [%3], %4;"
                 :: "r"(dst), "l"(src), "r"(bytes), "r"(bar), "l"(EVICT_FIRST) : "memory");
}
__device__ __forceinline__ void tile_g2s(uint32_t dst, const CUtensorMap* map, int x, int y, uint32_t bar) {
    asm volatile("cp.async.bulk.tensor.2d.shared::cluster.global.mbarrier::complete_tx::bytes [%0], [%1, {%2, %3}], [%4];"
                 :: "r"(dst), "l"(map), "r"(x), "r"(y), "r"(bar) : "memory");
}
__device__ __forceinline__ void lines_g2s(uint32_t dst, const CUtensorMap* map, int line0, uint32_t bar) {
    asm volatile("cp.async.bulk.tensor.2d.shared::cluster.global.mbarrier::complete_tx::bytes.L2::cache_hint [%0], [%1, {%2, %3}], [%4], %5;"
                 :: "r"(dst), "l"(map), "r"(0), "r"(line0), "r"(bar), "l"(EVICT_FIRST) : "memory");
}
__device__ __forceinline__ uint32_t now_ns() {
    uint32_t t;
    asm volatile("mov.u32 %0, %globaltimer_lo;" : "=r"(t));
    return t;
}
__device__ __forceinline__ bool elect() {
    uint32_t p;
    asm volatile("{\n.reg .pred P;\nelect.sync _|P, 0xffffffff;\nselp.u32 %0, 1, 0, P;\n}" : "=r"(p));
    return p;
}
__device__ __forceinline__ void mma(float (&d)[4], uint32_t a0, uint32_t a1, uint32_t a2, uint32_t a3, uint32_t b0, uint32_t b1) {
    asm volatile("mma.sync.aligned.m16n8k16.row.col.f32.bf16.bf16.f32 {%0,%1,%2,%3}, {%4,%5,%6,%7}, {%8,%9}, {%0,%1,%2,%3};"
                 : "+f"(d[0]), "+f"(d[1]), "+f"(d[2]), "+f"(d[3])
                 : "r"(a0), "r"(a1), "r"(a2), "r"(a3), "r"(b0), "r"(b1));
}
template <int N>
__device__ __forceinline__ void zero(float (&d)[N][4]) {
#pragma unroll
    for (int i = 0; i < N; i++) d[i][0] = d[i][1] = d[i][2] = d[i][3] = 0.f;
}
__device__ __forceinline__ uint4 lds128(uint32_t addr) {
    uint4 v;
    asm volatile("ld.shared.v4.u32 {%0,%1,%2,%3}, [%4];" : "=r"(v.x), "=r"(v.y), "=r"(v.z), "=r"(v.w) : "r"(addr) : "memory");
    return v;
}
__device__ __forceinline__ float2 lds64f(uint32_t addr) {
    float2 v;
    asm volatile("ld.shared.v2.f32 {%0,%1}, [%2];" : "=f"(v.x), "=f"(v.y) : "r"(addr) : "memory");
    return v;
}
__device__ __forceinline__ uint32_t lds32(uint32_t addr) {
    uint32_t v;
    asm volatile("ld.shared.u32 %0, [%1];" : "=r"(v) : "r"(addr) : "memory");
    return v;
}
__device__ __forceinline__ void sts64(uint32_t addr, uint32_t x, uint32_t y) {
    asm volatile("st.shared.v2.u32 [%0], {%1,%2};" :: "r"(addr), "r"(x), "r"(y) : "memory");
}
__device__ __forceinline__ void sts32(uint32_t addr, float x) {
    asm volatile("st.shared.f32 [%0], %1;" :: "r"(addr), "f"(x) : "memory");
}
__device__ __forceinline__ uint4 ldsm4t(uint32_t addr) {
    uint4 v;
    asm volatile("ldmatrix.sync.aligned.m8n8.x4.trans.shared.b16 {%0,%1,%2,%3}, [%4];"
                 : "=r"(v.x), "=r"(v.y), "=r"(v.z), "=r"(v.w) : "r"(addr) : "memory");
    return v;
}
__device__ __forceinline__ float fsel(float a, float b, uint32_t pick_b) {
    float r;
    asm("{\n.reg .pred s;\nsetp.ne.u32 s, %3, 0;\nselp.f32 %0, %2, %1, s;\n}" : "=f"(r) : "f"(a), "f"(b), "r"(pick_b));
    return r;
}
__device__ __forceinline__ uint32_t pack_bf16(float x, float y) {
    uint32_t r;
    asm("cvt.rn.bf16x2.f32 %0, %1, %2;" : "=r"(r) : "f"(y), "f"(x));
    return r;
}
__device__ __forceinline__ void split2(float x, float y, uint32_t& hi, uint32_t& lo) {
    hi = pack_bf16(x, y);
    lo = pack_bf16(x - __uint_as_float(hi << 16), y - __uint_as_float(hi & 0xffff0000u));
}
__device__ __forceinline__ uint32_t word(const uint4& v, int i) { return i == 0 ? v.x : i == 1 ? v.y : i == 2 ? v.z : v.w; }

__device__ __forceinline__ void red_add2(void* p, float x, float y) {
    asm volatile("red.relaxed.gpu.global.add.v2.f32 [%0], {%1,%2};" :: "l"(p), "f"(x), "f"(y) : "memory");
}
__device__ __forceinline__ void red_add4(void* p, float x, float y, float z, float w) {
    asm volatile("red.relaxed.gpu.global.add.v4.f32 [%0], {%1,%2,%3,%4};" :: "l"(p), "f"(x), "f"(y), "f"(z), "f"(w) : "memory");
}
__device__ __forceinline__ float4 ld_relaxed16(const void* p) {
    float4 r;
    asm volatile("{\n.reg .b128 u;\n.reg .b64 a, b;\nld.relaxed.gpu.global.b128 u, [%4];\nmov.b128 {a, b}, u;\n"
                 "mov.b64 {%0, %1}, a;\nmov.b64 {%2, %3}, b;\n}"
                 : "=f"(r.x), "=f"(r.y), "=f"(r.z), "=f"(r.w) : "l"(p) : "memory");
    return r;
}

__global__ void __launch_bounds__(NWARPS * 32, 1)
linformer_decode_kernel(const __nv_bfloat16* __restrict__ k, const __nv_bfloat16* __restrict__ q,
                        __nv_bfloat16* __restrict__ out, unsigned char* __restrict__ acc_all, int period_ns,
                        const __grid_constant__ CUtensorMap vmap, const __grid_constant__ CUtensorMap smap,
                        const __grid_constant__ CUtensorMap emap, const __grid_constant__ CUtensorMap fmap) {
    extern __shared__ __align__(1024) unsigned char smem[];
    const uint32_t sb = smem_u32(smem);
    const uint32_t bars = sb + OFF_BAR;
    const int grp = (blockIdx.x >> 2) & (NG - 1), c = (blockIdx.x & 3) + (blockIdx.x >> 5) * 4;

    {
        const uint32_t ofs = (grp * SKV + c * 64) * ROWB + (threadIdx.x >> 5) * (STAGE_B / NWARPS);
        if (elect()) asm volatile("cp.async.bulk.prefetch.L2.global [%0], %1;" :: "l"((const char*)k + ofs), "r"(STAGE_B / NWARPS) : "memory");
    }
    if (threadIdx.x < 32) {
        const bool leader = elect();
        auto issue_k = [&](int s, int slot) {
            const int row = (grp + (s >> 2) * NG) * SKV + (s & 3) * 1024 + c * 64;
            bulk_g2s(sb + slot * STAGE_B, (const char*)k + (size_t)row * ROWB, STAGE_B, bars + (B_FULL + s) * 8);
        };
        if (leader) {
            mbar_arm(bars + B_FULL * 8, STAGE_B);
            issue_k(0, 0);
        }
        const uint32_t t0 = now_ns();
        __syncthreads();
        if (leader) {
#pragma unroll
            for (int j = 0; j < HPC; j++) bulk_g2s(sb + OFF_Q + j * ROWB, q + (j * NG + grp) * DH, ROWB, bars + B_E * 8);
#pragma unroll
            for (int w = 0; w < 4; w++) tile_g2s(sb + OFF_EF + w * TILE_B, &emap, w * 1024 + c * 64, 0, bars + B_E * 8);
            issue_k(1, 1);
#pragma unroll
            for (int w = 0; w < 4; w++)
                tile_g2s(sb + OFF_EF + (4 + w) * TILE_B, &fmap, w * 1024 + c * (w < 3 ? 64 : 32), 0, bars + B_F * 8);
            issue_k(2, 2);
#pragma unroll 1
            for (int w = 0; w < 8; w++) tile_g2s(sb + OFF_G + w * TILE_B, &fmap, TAIL_ROW + w * 64, 0, bars + B_G * 8);

            uint32_t fly = 7, scan = fly;
            uint32_t due = t0 + 3 * period_ns - LEAD_NS;
#pragma unroll 1
            for (int u = 3, slot = 3, it = 0; u < NUNIT && it < SPIN_LIMIT * 64; it++) {
                const int limit = (int)(now_ns() - due) <= 0 ? FLY_MIN : u < NSTAGE ? FLY_MAX : NUNIT;
                if (__popc(fly) < limit) {
                    const uint32_t bar = bars + (B_FULL + u) * 8;
                    mbar_wait(bars + (B_FREE + (u < NSTAGE ? u : (NSTAGE + u) >> 1)) * 8);
                    if (u < 16) {
                        issue_k(u, slot);
                        due += period_ns;
                    } else if (u < NSTAGE) {
                        const bool full = (u & 3) != 3;
                        const int line = ((grp + ((u >> 2) & 3) * NG) * SKV + (u & 3) * 1024 + c * (full ? 64 : 32)) * 3;
                        lines_g2s(sb + slot * STAGE_B, &vmap, line, bar);
                        if (full) lines_g2s(sb + slot * STAGE_B + STAGE_B / 2, &vmap, line + 96, bar);
                        due += full ? period_ns : period_ns / 2;
                        if (u == NSTAGE - 1) due += TAIL_LAG_NS;
                    } else {
                        tile_g2s(sb + TAIL_SLOT * STAGE_B + (u - NSTAGE) * 128 * SLICE_B, &smap, (c & 3) * 48,
                                 (grp + (c >> 2) * NG) * SKV + TAIL_ROW + (u - NSTAGE) * 128, bar);
                        due += period_ns / 2;
                    }
                    fly |= 1u << (u & 31);
                    u++;
                    if (++slot == NS) slot = 0;
                } else {
                    if (!scan) scan = fly;
                    const int m = __ffs(scan) - 1;
                    scan &= scan - 1;
                    if (mbar_test(bars + (B_FULL + (u > NSTAGE && m < 4 ? NSTAGE + m : m)) * 8)) fly ^= 1u << m;
                }
            }
        }
        return;
    }

    const int warp = __shfl_sync(0xffffffffu, threadIdx.x >> 5, 0), lane = threadIdx.x & 31;
    const int g = lane >> 2, t = lane & 3;
    unsigned char* const acc_g = acc_all + grp * ACC_GROUP;
    unsigned char* const score_p = acc_g + acc_line(16 + (lane >> 3)) + (lane & 7) * 16;

    if (warp <= NV) {
        const int vw = warp - 1;
        if (elect()) {
#pragma unroll
            for (int i = 0; i < 5; i++) {
                const int u = vw * 5 + i + 1;
                mbar_arm(bars + (B_FULL + u) * 8, (u & 19) == 19 ? STAGE_B / 2 : STAGE_B);
                mbar_init(bars + (B_FREE + u + 2) * 8, NV);
            }
        }
        __syncthreads();

        if (vw < 4) {
            const int w = vw;
            const uint32_t tile = sb + OFF_EF + w * TILE_B;
            uint32_t ef[4][4][4];
            mbar_wait(bars + B_E * 8);
#pragma unroll
            for (int i = 0; i < 8; i++) {
                const uint4 ea = lds128(tile + (i * 8 + g) * 128 + (((2 * t) ^ g) << 4));
                const uint4 eb = lds128(tile + (i * 8 + g) * 128 + (((2 * t + 1) ^ g) << 4));
#pragma unroll
                for (int ks = 0; ks < 4; ks++) { ef[i >> 1][ks][i & 1] = word(ea, ks); ef[i >> 1][ks][2 + (i & 1)] = word(eb, ks); }
            }
            __syncwarp();
            if (lane == 0) mbar_arrive(bars + (B_FREE + (w < 2 ? 3 : 4)) * 8, w < 2 ? NV / 2 : NV / 3);

            const uint32_t kofs = sb + ((g & 3) * 16 + (g >> 2) * 8) * ROWB + t * 16 + (g & 1) * 64;
            const uint32_t qofs = sb + OFF_Q + t * 16 + (g & 1) * 4 + (g & 2) * 32;
            const uint32_t m0 = (g == t) ? 0xffffffffu : 0u, m1 = (g == t + 4) ? 0xffffffffu : 0u;
#pragma unroll 1
            for (int j = 0; j < HPC; j++) {
                const int s = j * 4 + w;
                uint32_t ka = kofs + (s % NS) * STAGE_B, qa = qofs + j * ROWB;
                mbar_wait(bars + (B_FULL + s) * 8);
                float d[8][4];
                zero(d);
#pragma unroll 1
                for (int i = 0; i < 3; i++, ka += 128, qa += 128) {
#pragma unroll
                    for (int h = 0; h < 2; h++) {
                        const uint32_t q0 = lds32(qa ^ (h * 64)), q1 = lds32((qa ^ (h * 64)) + 8);
#pragma unroll
                        for (int u = 0; u < 8; u++) {
                            const uint4 kv = lds128((ka ^ (h * 64)) + u * ROWB);
                            mma(d[u], kv.x, kv.y, kv.z, kv.w, q0, q1);
                        }
                    }
                }
                __syncwarp();
                if (lane == 0) mbar_arrive(bars + (B_FREE + s + NS) * 8, NV);

                float d2[4][4];
                zero(d2);
#pragma unroll
                for (int ks = 0; ks < 4; ks++) {
                    uint32_t hi, lo;
                    split2(d[2 * ks][0] + d[2 * ks][3], d[2 * ks + 1][0] + d[2 * ks + 1][3], hi, lo);
#pragma unroll
                    for (int i = 0; i < 4; i++) mma(d2[i], ef[i][ks][0], ef[i][ks][1], ef[i][ks][2], ef[i][ks][3], hi & m0, hi & m1);
#pragma unroll
                    for (int i = 0; i < 4; i++) mma(d2[i], ef[i][ks][0], ef[i][ks][1], ef[i][ks][2], ef[i][ks][3], lo & m0, lo & m1);
                }
                float x[4], y[4];
#pragma unroll
                for (int i = 0; i < 4; i++) { x[i] = d2[i][0] + d2[i][1]; y[i] = d2[i][2] + d2[i][3]; }
#pragma unroll
                for (int i = 0; i < 2; i++) {
                    x[i] = fsel(x[i], x[i + 2], t & 2) + __shfl_xor_sync(0xffffffffu, fsel(x[i + 2], x[i], t & 2), 2);
                    y[i] = fsel(y[i], y[i + 2], t & 2) + __shfl_xor_sync(0xffffffffu, fsel(y[i + 2], y[i], t & 2), 2);
                }
                const float sx = fsel(x[0], x[1], t & 1) + __shfl_xor_sync(0xffffffffu, fsel(x[1], x[0], t & 1), 1);
                const float sy = fsel(y[0], y[1], t & 1) + __shfl_xor_sync(0xffffffffu, fsel(y[1], y[0], t & 1), 1);
                sts32(sb + OFF_S + (j * 4 + w) * 256 + (16 * t + g) * 4, sx);
                sts32(sb + OFF_S + (j * 4 + w) * 256 + (16 * t + 8 + g) * 4, sy);
                __syncwarp();
                if (lane == 0) mbar_arrive(bars + (B_S + j) * 8);
            }
        }

        const int mat = lane >> 3, mi = lane & 7;
        const uint32_t wofs = sb + OFF_W + (g & 1) * 64 + t * 16;
        {
            uint32_t off[2];
#pragma unroll
            for (int u = 0; u < 2; u++) {
                const int cc = vw * 4 + u * 2 + (mat & 1), blk = cc >> 3;
                off[u] = sb + ((mat >> 1) * 8 + mi) * ROWB + blk * 128 + (((cc & 7) ^ ((3 * mi + blk) & 7)) << 4);
            }
            const int col = vw * 32 + (t & 1) * 16 + (t >> 1) * 8 + g;
            unsigned char* accp = acc_g + acc_line(col >> 4) + (col & 15) * 8;
            float acc[2][4];
            auto rows32 = [&](uint32_t ofs, const uint4& wb) {
#pragma unroll
                for (int x = 0; x < 2; x++)
#pragma unroll
                    for (int u = 0; u < 2; u++) {
                        const uint4 a = ldsm4t(off[u] + ofs + x * 16 * ROWB);
                        mma(acc[u], a.x, a.y, a.z, a.w, word(wb, 2 * x), word(wb, 2 * x + 1));
                    }
            };
#pragma unroll 1
            for (int s = 16, slot = 16 % NS; s < NSTAGE; s++) {
                if ((s & 3) == 0) {
                    zero(acc);
                    mbar_wait(bars + (B_W - 4 + (s >> 2)) * 8);
                }
                const uint4 w0 = lds128(wofs + (s - 16) * 256), w1 = lds128(wofs + (s - 16) * 256 + 128);
                mbar_wait(bars + (B_FULL + s) * 8);
                if ((s & 3) != 3) {
                    rows32(slot * STAGE_B, w0);
                    rows32(slot * STAGE_B + STAGE_B / 2, w1);
                } else {
                    rows32(slot * STAGE_B, w0);
                    red_add2(accp, fsel(fsel(acc[0][0] + acc[0][1], acc[0][2] + acc[0][3], t & 2),
                                        fsel(acc[1][0] + acc[1][1], acc[1][2] + acc[1][3], t & 2), t & 1), 1.f);
                    accp += ACC_SET;
                }
                __syncwarp();
                if (lane == 0 && (s < 28 || s == NSTAGE - 1)) mbar_arrive(bars + (s < 28 ? B_FREE + s + NS : B_O) * 8);
                if (++slot == NS) slot = 0;
            }
        }

        if (vw < 3) {
            uint32_t fa = sb + TAIL_SLOT * STAGE_B + ((mat >> 1) * 8 + mi) * SLICE_B + (2 * vw + ((mat & 1) ^ (mi >> 2))) * 16;
            const int tcol = vw * 16 + (t & 1) * 8 + g;
            __nv_bfloat16* outp = out + (grp + (c >> 2) * NG) * DH + (c & 3) * 48 + tcol;
            asm volatile("" : "+l"(outp));
            float acc[2][4];
            zero(acc);
            auto unit = [&](int i) {
                uint4 wb[4];
#pragma unroll
                for (int x = 0; x < 4; x++) wb[x] = lds128(wofs + HPC * 1024 + i * 512 + x * 128);
                mbar_wait(bars + (B_FULL + NSTAGE + i) * 8);
#pragma unroll
                for (int x = 0; x < 8; x++) {
                    const uint4 a = ldsm4t(fa + x * 16 * SLICE_B);
                    const bool sw = t >= 2;
                    mma(acc[x & 1], sw ? a.y : a.x, sw ? a.x : a.y, sw ? a.w : a.z, sw ? a.z : a.w,
                        word(wb[x >> 1], (x & 1) * 2), word(wb[x >> 1], (x & 1) * 2 + 1));
                }
                fa += 128 * SLICE_B;
            };
            mbar_wait(bars + (B_W + HPC) * 8);
#pragma unroll 1
            for (int i = 0; i < 3; i++) unit(i);
            const bool early = mbar_test(bars + B_T * 8);
            float tot = early ? __uint_as_float(lds32(sb + OFF_T + tcol * 4)) : 0.f;
            unit(3);
            if (!early) {
                mbar_wait(bars + B_T * 8);
                tot = __uint_as_float(lds32(sb + OFF_T + tcol * 4));
            }
            const float o = (tot + fsel(acc[0][0] + acc[0][1], acc[0][2] + acc[0][3], t & 1)) +
                            fsel(acc[1][0] + acc[1][1], acc[1][2] + acc[1][3], t & 1);
            asm volatile("{\n.reg .pred p;\n.reg .b16 h;\ncvt.rn.bf16.f32 h, %1;\nsetp.lt.u32 p, %2, 2;\n@p st.global.b16 [%0], h;\n}"
                         :: "l"(outp), "f"(o), "r"(t) : "memory");
        }
    } else if (warp <= NV + 4) {
        const int w = warp - (NV + 1);
        if (elect()) {
            mbar_init(bars + (B_S + w) * 8, 4);
            mbar_init(bars + (B_P + w) * 8, 1);
            mbar_init(bars + (B_W + w) * 8, 4);
            mbar_arm(bars + (B_FULL + NSTAGE + w) * 8, 128 * SLICE_B);
        }
        __syncthreads();
        uint32_t fb[8][8];
#pragma unroll 1
        for (int j = 0; j < HPC + 2; j++) {
            if (j == 0 || j >= HPC) {
                const uint32_t tile = sb + (j == 0 ? OFF_EF + 4 * TILE_B : OFF_G + (j - HPC) * 4 * TILE_B) + w * TILE_B;
                mbar_wait(bars + (j == 0 ? B_F : B_G) * 8);
#pragma unroll
                for (int x = 0; x < 8; x++) {
                    const uint4 f0 = lds128(tile + (x * 8 + 2 * t) * 128 + ((g ^ (2 * t)) << 4));
                    const uint4 f1 = lds128(tile + (x * 8 + 2 * t + 1) * 128 + ((g ^ (2 * t + 1)) << 4));
#pragma unroll
                    for (int i = 0; i < 8; i++) fb[i][x] = __byte_perm(word(f0, i >> 1), word(f1, i >> 1), (i & 1) ? 0x7632 : 0x5410);
                }
                __syncwarp();
                if (j == 0 && lane == 0) mbar_arrive(bars + (B_FREE + (w == 0 ? 4 : 5)) * 8, NV / 3);
            }
            if (j == w) {
                mbar_wait(bars + (B_FULL + READ_AT + 4 * j) * 8);
                float4 sc;
#pragma unroll 1
                for (int it = 0;; it++) {
                    sc = ld_relaxed16(score_p + j * ACC_SET);
                    if (__all_sync(0xffffffffu, sc.z == (float)NC)) break;
                    if (it > SPIN_LIMIT) __trap();
                    __nanosleep(500);
                }
                const float scale = 0.07216878364870322f;
                sc.x *= scale; sc.y *= scale;
                float m = fmaxf(sc.x, sc.y);
#pragma unroll
                for (int o = 16; o > 0; o >>= 1) m = fmaxf(m, __shfl_xor_sync(0xffffffffu, m, o));
                const float e0 = expf(sc.x - m), e1 = expf(sc.y - m);
                float sum = e0 + e1;
#pragma unroll
                for (int o = 16; o > 0; o >>= 1) sum += __shfl_xor_sync(0xffffffffu, sum, o);
                const float inv = 1.0f / sum;
                uint32_t hi, lo;
                split2(e0 * inv, e1 * inv, hi, lo);
                sts64(sb + OFF_P + j * 256 + (g >> 1) * 64 + t * 16 + (g & 1) * 8, hi, lo);
                __syncwarp();
                if (lane == 0) mbar_arrive(bars + (B_P + j) * 8);
            }
            const int pj = j < HPC ? j : c >> 2;
            mbar_wait(bars + (B_P + pj) * 8);
            float d[8][4];
            zero(d);
#pragma unroll
            for (int ks = 0; ks < 4; ks++) {
                const uint4 a = lds128(sb + OFF_P + pj * 256 + ks * 64 + t * 16);
#pragma unroll
                for (int i = 0; i < 8; i++) mma(d[i], a.x, a.y, a.z, a.w, fb[i][2 * ks], fb[i][2 * ks + 1]);
            }
            float x[8], y[8];
#pragma unroll
            for (int i = 0; i < 8; i++) { x[i] = d[i][0] + d[i][2]; y[i] = d[i][1] + d[i][3]; }
#pragma unroll
            for (int i = 0; i < 4; i++) { x[i] = fsel(x[i], x[i + 4], g & 4); y[i] = fsel(y[i], y[i + 4], g & 4); }
#pragma unroll
            for (int i = 0; i < 2; i++) { x[i] = fsel(x[i], x[i + 2], g & 2); y[i] = fsel(y[i], y[i + 2], g & 2); }
            uint32_t xh, xl, yh, yl;
            split2(x[0], x[1], xh, xl);
            split2(y[0], y[1], yh, yl);
            sts64(sb + OFF_W + (j * 4 + w) * 256 + (t >> 1) * 128 + (g & 1) * 64 + (g >> 1) * 16 + (t & 1) * 8,
                  (g & 1) ? xl : xh, (g & 1) ? yl : yh);
            __syncwarp();
            if (lane == 0) mbar_arrive(bars + (B_W + min(j, HPC)) * 8);
        }
    } else {
        if (elect()) {
            asm volatile("prefetch.tensormap [%0];" :: "l"(&emap) : "memory");
            asm volatile("prefetch.tensormap [%0];" :: "l"(&fmap) : "memory");
            asm volatile("prefetch.tensormap [%0];" :: "l"(&vmap) : "memory");
            asm volatile("prefetch.tensormap [%0];" :: "l"(&smap) : "memory");
            mbar_arm(bars + B_E * 8, 4 * TILE_B + HPC * ROWB);
            mbar_arm(bars + B_F * 8, 4 * TILE_B);
            mbar_arm(bars + B_G * 8, 8 * TILE_B);
            mbar_arm(bars + (B_FULL + NSTAGE - 1) * 8, STAGE_B / 2);
            mbar_init(bars + (B_FREE + NSTAGE + 1) * 8, NV);
            mbar_init(bars + (B_W + HPC) * 8, 8);
            mbar_init(bars + B_O * 8, NV);
            mbar_init(bars + B_T * 8, 1);
        }
        __syncthreads();
#pragma unroll 1
        for (int j = 0; j < HPC; j++) {
            mbar_wait(bars + (B_S + j) * 8);
            const float2 p0 = lds64f(sb + OFF_S + (j * 4 + 0) * 256 + lane * 8);
            const float2 p1 = lds64f(sb + OFF_S + (j * 4 + 1) * 256 + lane * 8);
            const float2 p2 = lds64f(sb + OFF_S + (j * 4 + 2) * 256 + lane * 8);
            const float2 p3 = lds64f(sb + OFF_S + (j * 4 + 3) * 256 + lane * 8);
            red_add4(score_p + j * ACC_SET, (p0.x + p1.x) + (p2.x + p3.x), (p0.y + p1.y) + (p2.y + p3.y), 1.f, 0.f);
        }
        unsigned char* tp = acc_g + (c >> 2) * ACC_SET + acc_line(lane < 24 ? (c & 3) * 3 + (lane >> 3) : 16 + (c & 3)) + (lane & 7) * 16;
        mbar_wait(bars + (c < 12 ? B_FULL + 30 : B_O) * 8);
        for (const uint32_t t1 = now_ns(); now_ns() - t1 < POLL_LAG_NS;) {}
        float4 r;
#pragma unroll 1
        for (int it = 0;; it++) {
            if (lane < 24) r = ld_relaxed16(tp);
            if (__all_sync(0xffffffffu, lane >= 24 || (r.y == (float)NC && r.w == (float)NC))) break;
            if (it > SPIN_LIMIT) __trap();
        }
        if (lane < 24) sts64(sb + OFF_T + lane * 8, __float_as_uint(r.x), __float_as_uint(r.z));
        __syncwarp();
        if (lane == 0) mbar_arrive(bars + B_T * 8);
        asm volatile("st.global.v4.u32 [%0], {%1,%1,%1,%1};" :: "l"(tp), "r"(0) : "memory");
    }
}

static CUtensorMap make_map(const void* p, uint64_t cols, uint64_t rows, uint32_t box_cols, uint32_t box_rows) {
    typedef CUresult (*EncodeFn)(CUtensorMap*, CUtensorMapDataType, cuuint32_t, void*, const cuuint64_t*, const cuuint64_t*,
                                 const cuuint32_t*, const cuuint32_t*, CUtensorMapInterleave, CUtensorMapSwizzle,
                                 CUtensorMapL2promotion, CUtensorMapFloatOOBfill);
    void* fn = nullptr;
    cudaDriverEntryPointQueryResult qr;
    cudaGetDriverEntryPoint("cuTensorMapEncodeTiled", &fn, cudaEnableDefault, &qr);
    CUtensorMap m;
    const cuuint64_t dims[2] = {cols, rows};
    const cuuint64_t strides[1] = {cols * 2};
    const cuuint32_t box[2] = {box_cols, box_rows};
    const cuuint32_t estr[2] = {1, 1};
    ((EncodeFn)fn)(&m, CU_TENSOR_MAP_DATA_TYPE_BFLOAT16, 2, (void*)p, dims, strides, box, estr, CU_TENSOR_MAP_INTERLEAVE_NONE,
                   box_cols == 64 ? CU_TENSOR_MAP_SWIZZLE_128B : CU_TENSOR_MAP_SWIZZLE_NONE,
                   box_cols == 64 ? CU_TENSOR_MAP_L2_PROMOTION_NONE : CU_TENSOR_MAP_L2_PROMOTION_L2_128B,
                   CU_TENSOR_MAP_FLOAT_OOB_FILL_NONE);
    return m;
}

}

extern "C" void kernel_launch(void* const* d_in, const int* in_sizes, int n_in, void* d_out, int out_size) {
    using namespace lf;
    void* acc = nullptr;
    cudaGetSymbolAddress(&acc, g_acc);
    acc = (void*)(((uintptr_t)acc + ACC_GROUP - 1) & ~(uintptr_t)(ACC_GROUP - 1));
    cudaFuncSetAttribute(linformer_decode_kernel, cudaFuncAttributeMaxDynamicSharedMemorySize, SMEM_BYTES);
    int dev = 0, mem_khz = 0, bus_bits = 0;
    cudaGetDevice(&dev);
    cudaDeviceGetAttribute(&mem_khz, cudaDevAttrMemoryClockRate, dev);
    cudaDeviceGetAttribute(&bus_bits, cudaDevAttrGlobalMemoryBusWidth, dev);
    const int period_ns = (int)((double)NCTA * STAGE_B / (0.9775 * 2e-6 * mem_khz * (bus_bits / 8)));
    cudaLaunchAttribute attr;
    attr.id = cudaLaunchAttributeCooperative;
    attr.val.cooperative = 1;
    cudaLaunchConfig_t cfg = {};
    cfg.gridDim = dim3(NCTA);
    cfg.blockDim = dim3(NWARPS * 32);
    cfg.dynamicSmemBytes = SMEM_BYTES;
    cfg.stream = cudaStreamPerThread;
    cfg.attrs = &attr;
    cfg.numAttrs = 1;
    cudaLaunchKernelEx(&cfg, linformer_decode_kernel,
                       (const __nv_bfloat16*)d_in[1], (const __nv_bfloat16*)d_in[0], (__nv_bfloat16*)d_out, (unsigned char*)acc, period_ns,
                       make_map(d_in[2], 64, (uint64_t)H * SKV * 3, 64, 96),
                       make_map(d_in[2], DH, (uint64_t)H * SKV, 48, 128),
                       make_map(d_in[3], SKV, 64, 64, 64), make_map(d_in[4], SKV, 64, 64, 64));
}
```

```cpp
#include <cuda.h>
#include <cuda_runtime.h>
#include <cuda_bf16.h>
#include <stdint.h>

namespace lf {

constexpr int H = 32, SKV = 4096, DH = 192;
constexpr int NCTA = 128;
constexpr int NC = 16;
constexpr int NG = 8;
constexpr int HPC = 4;
constexpr int ROWB = DH * 2;
constexpr int STAGE_B = 64 * ROWB;
constexpr int NS = 6;
constexpr int NSTAGE = 32;
constexpr int NUNIT = NSTAGE + 4;
constexpr int TAIL_ROW = SKV - 512;
constexpr int SLICE_B = 96;
constexpr int TAIL_SLOT = NSTAGE % NS;
constexpr int NWARPS = 9;

constexpr int FLY_MIN = 2, FLY_MAX = 5;
constexpr int LEAD_NS = 450;
constexpr int TAIL_LAG_NS = 180;
constexpr int POLL_LAG_NS = 200;
constexpr int READ_AT = 8;

constexpr int TILE_B = 64 * 128;
constexpr int OFF_EF = 3 * STAGE_B + TILE_B;
constexpr int OFF_G = NS * STAGE_B;
constexpr int OFF_W = OFF_G + 8 * TILE_B;
constexpr int OFF_P = OFF_W + 6144;
constexpr int OFF_S = OFF_P + 1024;
constexpr int OFF_Q = OFF_S + 4096;
constexpr int OFF_T = OFF_Q + 1536;
constexpr int OFF_T0 = OFF_T + 192;
constexpr int OFF_BAR = OFF_T0 + 8;
constexpr int B_FULL = 0, B_FREE = NUNIT - 3, B_S = 67, B_P = 71, B_W = 75, B_O = 80, B_T = 81, B_E = 82, B_F = 83, B_G = 84;
constexpr int SMEM_BYTES = OFF_BAR + 85 * 8;

constexpr int SPIN_LIMIT = 1 << 20;

constexpr int ACC_GROUP = 65536, ACC_SET = 4096;
__device__ unsigned char g_acc[(NG + 1) * ACC_GROUP];
__device__ __forceinline__ int acc_line(int i) { return (i & 1) * 256 + ((i >> 1) & 3) * 1024 + (i >> 3) * 16384; }

__device__ __forceinline__ uint32_t smem_u32(const void* p) { return (uint32_t)__cvta_generic_to_shared(p); }
__device__ __forceinline__ void mbar_init(uint32_t bar, uint32_t cnt) {
    asm volatile("mbarrier.init.shared::cta.b64 [%0], %1;" :: "r"(bar), "r"(cnt) : "memory");
}
__device__ __forceinline__ void mbar_arm(uint32_t bar, uint32_t bytes) {
    mbar_init(bar, 1);
    asm volatile("mbarrier.arrive.expect_tx.shared::cta.b64 _, [%0], %1;" :: "r"(bar), "r"(bytes) : "memory");
}
__device__ __forceinline__ void mbar_arrive(uint32_t bar, uint32_t n = 1) {
    asm volatile("mbarrier.arrive.shared::cta.b64 _, [%0], %1;" :: "r"(bar), "r"(n) : "memory");
}
__device__ __forceinline__ bool mbar_test(uint32_t bar) {
    uint32_t ok;
    asm volatile("{\n.reg .pred p;\nmbarrier.test_wait.parity.shared::cta.b64 p, [%1], 0;\nselp.u32 %0, 1, 0, p;\n}"
                 : "=r"(ok) : "r"(bar) : "memory");
    return ok;
}
__device__ __forceinline__ void mbar_wait(uint32_t bar) {
    asm volatile("{\n.reg .pred p, q;\n.reg .u32 n;\nmov.u32 n, 0;\n"
                 "LF_WAIT_%=:\n"
                 "mbarrier.try_wait.parity.shared::cta.b64 p, [%0], 0;\n"
                 "add.u32 n, n, 1;\n"
                 "setp.lt.u32 q, n, %1;\n"
                 "and.pred q, q, !p;\n"
                 "@q bra LF_WAIT_%=;\n}"
                 :: "r"(bar), "n"(SPIN_LIMIT) : "memory");
}
__device__ __forceinline__ uint64_t evict_first() {
    uint64_t pol;
    asm("createpolicy.fractional.L2::evict_first.b64 %0, 1.0;" : "=l"(pol));
    return pol;
}
__device__ __forceinline__ void bulk_g2s(uint32_t dst, const void* src, uint32_t bytes, uint32_t bar) {
    asm volatile("cp.async.bulk.shared::cluster.global.mbarrier::complete_tx::bytes.L2::cache_hint [%0], [%1], %2, [%3], %4;"
                 :: "r"(dst), "l"(src), "r"(bytes), "r"(bar), "l"(evict_first()) : "memory");
}
__device__ __forceinline__ void tile_g2s(uint32_t dst, const CUtensorMap* map, int x, int y, uint32_t bar) {
    asm volatile("cp.async.bulk.tensor.2d.shared::cluster.global.mbarrier::complete_tx::bytes [%0], [%1, {%2, %3}], [%4];"
                 :: "r"(dst), "l"(map), "r"(x), "r"(y), "r"(bar) : "memory");
}
__device__ __forceinline__ void lines_g2s(uint32_t dst, const CUtensorMap* map, int line0, uint32_t bar) {
    asm volatile("cp.async.bulk.tensor.2d.shared::cluster.global.mbarrier::complete_tx::bytes.L2::cache_hint [%0], [%1, {%2, %3}], [%4], %5;"
                 :: "r"(dst), "l"(map), "r"(0), "r"(line0), "r"(bar), "l"(evict_first()) : "memory");
}
__device__ __forceinline__ uint32_t now_ns() {
    uint32_t t;
    asm volatile("mov.u32 %0, %globaltimer_lo;" : "=r"(t));
    return t;
}
__device__ __forceinline__ bool elect() {
    uint32_t p;
    asm volatile("{\n.reg .pred P;\nelect.sync _|P, 0xffffffff;\nselp.u32 %0, 1, 0, P;\n}" : "=r"(p));
    return p;
}
__device__ __forceinline__ void mma(float (&d)[4], uint32_t a0, uint32_t a1, uint32_t a2, uint32_t a3, uint32_t b0, uint32_t b1) {
    asm volatile("mma.sync.aligned.m16n8k16.row.col.f32.bf16.bf16.f32 {%0,%1,%2,%3}, {%4,%5,%6,%7}, {%8,%9}, {%0,%1,%2,%3};"
                 : "+f"(d[0]), "+f"(d[1]), "+f"(d[2]), "+f"(d[3])
                 : "r"(a0), "r"(a1), "r"(a2), "r"(a3), "r"(b0), "r"(b1));
}
template <int N>
__device__ __forceinline__ void zero(float (&d)[N][4]) {
#pragma unroll
    for (int i = 0; i < N; i++) d[i][0] = d[i][1] = d[i][2] = d[i][3] = 0.f;
}
__device__ __forceinline__ uint4 lds128(uint32_t addr) {
    uint4 v;
    asm volatile("ld.shared.v4.u32 {%0,%1,%2,%3}, [%4];" : "=r"(v.x), "=r"(v.y), "=r"(v.z), "=r"(v.w) : "r"(addr) : "memory");
    return v;
}
__device__ __forceinline__ float2 lds64f(uint32_t addr) {
    float2 v;
    asm volatile("ld.shared.v2.f32 {%0,%1}, [%2];" : "=f"(v.x), "=f"(v.y) : "r"(addr) : "memory");
    return v;
}
__device__ __forceinline__ uint32_t lds32(uint32_t addr) {
    uint32_t v;
    asm volatile("ld.shared.u32 %0, [%1];" : "=r"(v) : "r"(addr) : "memory");
    return v;
}
__device__ __forceinline__ void sts64(uint32_t addr, uint32_t x, uint32_t y) {
    asm volatile("st.shared.v2.u32 [%0], {%1,%2};" :: "r"(addr), "r"(x), "r"(y) : "memory");
}
__device__ __forceinline__ void sts32(uint32_t addr, float x) {
    asm volatile("st.shared.f32 [%0], %1;" :: "r"(addr), "f"(x) : "memory");
}
__device__ __forceinline__ uint4 ldsm4t(uint32_t addr) {
    uint4 v;
    asm volatile("ldmatrix.sync.aligned.m8n8.x4.trans.shared.b16 {%0,%1,%2,%3}, [%4];"
                 : "=r"(v.x), "=r"(v.y), "=r"(v.z), "=r"(v.w) : "r"(addr) : "memory");
    return v;
}
__device__ __forceinline__ float fsel(float a, float b, uint32_t pick_b) {
    float r;
    asm("{\n.reg .pred s;\nsetp.ne.u32 s, %3, 0;\nselp.f32 %0, %2, %1, s;\n}" : "=f"(r) : "f"(a), "f"(b), "r"(pick_b));
    return r;
}
__device__ __forceinline__ uint32_t pack_bf16(float x, float y) {
    uint32_t r;
    asm("cvt.rn.bf16x2.f32 %0, %1, %2;" : "=r"(r) : "f"(y), "f"(x));
    return r;
}
__device__ __forceinline__ void split2(float x, float y, uint32_t& hi, uint32_t& lo) {
    hi = pack_bf16(x, y);
    lo = pack_bf16(x - __uint_as_float(hi << 16), y - __uint_as_float(hi & 0xffff0000u));
}
__device__ __forceinline__ uint32_t word(const uint4& v, int i) { return i == 0 ? v.x : i == 1 ? v.y : i == 2 ? v.z : v.w; }

__device__ __forceinline__ void contribute(void* p, float x, float y) {
    asm volatile("red.relaxed.gpu.global.add.v4.f32 [%0], {%1,%2,%3,%4};" :: "l"(p), "f"(x), "f"(y), "f"(1.f), "f"(0.f) : "memory");
}
__device__ __forceinline__ float4 ld_relaxed16(const void* p) {
    float4 r;
    asm volatile("{\n.reg .b128 u;\n.reg .b64 a, b;\nld.relaxed.gpu.global.b128 u, [%4];\nmov.b128 {a, b}, u;\n"
                 "mov.b64 {%0, %1}, a;\nmov.b64 {%2, %3}, b;\n}"
                 : "=f"(r.x), "=f"(r.y), "=f"(r.z), "=f"(r.w) : "l"(p) : "memory");
    return r;
}

__global__ void __launch_bounds__(NWARPS * 32, 1)
linformer_decode_kernel(const __nv_bfloat16* __restrict__ k, const __nv_bfloat16* __restrict__ q,
                        __nv_bfloat16* __restrict__ out, unsigned char* __restrict__ acc_all, int period_ns,
                        const __grid_constant__ CUtensorMap vmap, const __grid_constant__ CUtensorMap smap,
                        const __grid_constant__ CUtensorMap emap, const __grid_constant__ CUtensorMap fmap) {
    extern __shared__ __align__(1024) unsigned char smem[];
    const uint32_t sb = smem_u32(smem);
    const uint32_t bars = sb + OFF_BAR;
    const int grp = (blockIdx.x >> 2) & (NG - 1), c = (blockIdx.x & 3) + (blockIdx.x >> 5) * 4;

    asm volatile("prefetch.global.L2 [%0];" :: "l"((const char*)k + (uint32_t)(((grp * 64 + c) * (STAGE_B / 64) + threadIdx.x) * 64)) : "memory");
    if (threadIdx.x < 32) {
        const bool leader = elect();
        auto issue_k = [&](int s, int slot) {
            const int row = (grp + (s >> 2) * NG) * SKV + (s & 3) * 1024 + c * 64;
            bulk_g2s(sb + slot * STAGE_B, (const char*)k + (size_t)row * ROWB, STAGE_B, bars + (B_FULL + s) * 8);
        };
        if (leader) {
            mbar_arm(bars + B_FULL * 8, STAGE_B);
            issue_k(0, 0);
            sts32(sb + OFF_T0, __uint_as_float(now_ns()));
        }
        __syncthreads();
        if (leader) {
#pragma unroll
            for (int j = 0; j < HPC; j++) bulk_g2s(sb + OFF_Q + j * ROWB, q + (j * NG + grp) * DH, ROWB, bars + B_E * 8);
#pragma unroll
            for (int w = 0; w < 4; w++) tile_g2s(sb + OFF_EF + w * TILE_B, &emap, w * 1024 + c * 64, 0, bars + B_E * 8);
            issue_k(1, 1);
#pragma unroll
            for (int w = 0; w < 4; w++)
                tile_g2s(sb + OFF_EF + (4 + w) * TILE_B, &fmap, w * 1024 + c * (w < 3 ? 64 : 32), 0, bars + B_F * 8);
            issue_k(2, 2);
#pragma unroll 1
            for (int w = 0; w < 8; w++) tile_g2s(sb + OFF_G + w * TILE_B, &fmap, TAIL_ROW + w * 64, 0, bars + B_G * 8);

            uint32_t fly = 7, scan = fly;
            uint32_t due = lds32(sb + OFF_T0) + 3 * period_ns - LEAD_NS;
#pragma unroll 1
            for (int u = 3, slot = 3, it = 0; u < NUNIT && it < SPIN_LIMIT * 64; it++) {
                const int limit = (int)(now_ns() - due) <= 0 ? FLY_MIN : u < NSTAGE ? FLY_MAX : NUNIT;
                if (__popc(fly) < limit) {
                    const uint32_t bar = bars + (B_FULL + u) * 8;
                    mbar_wait(bars + (B_FREE + (u < NSTAGE ? u : (NSTAGE + u) >> 1)) * 8);
                    if (u < 16) {
                        issue_k(u, slot);
                        due += period_ns;
                    } else if (u < NSTAGE) {
                        const bool full = (u & 3) != 3;
                        const int line = ((grp + ((u >> 2) & 3) * NG) * SKV + (u & 3) * 1024 + c * (full ? 64 : 32)) * 3;
                        lines_g2s(sb + slot * STAGE_B, &vmap, line, bar);
                        if (full) lines_g2s(sb + slot * STAGE_B + STAGE_B / 2, &vmap, line + 96, bar);
                        due += full ? period_ns : period_ns / 2;
                        if (u == NSTAGE - 1) due += TAIL_LAG_NS;
                    } else {
                        tile_g2s(sb + TAIL_SLOT * STAGE_B + (u - NSTAGE) * 128 * SLICE_B, &smap, (c & 3) * 48,
                                 (grp + (c >> 2) * NG) * SKV + TAIL_ROW + (u - NSTAGE) * 128, bar);
                        due += period_ns / 2;
                    }
                    fly |= 1u << (u & 31);
                    u++;
                    if (++slot == NS) slot = 0;
                } else {
                    if (!scan) scan = fly;
                    const int m = __ffs(scan) - 1;
                    scan &= scan - 1;
                    if (mbar_test(bars + (B_FULL + (u > NSTAGE && m < 4 ? NSTAGE + m : m)) * 8)) fly ^= 1u << m;
                }
            }
        }
        return;
    }

    const int warp = __shfl_sync(0xffffffffu, threadIdx.x >> 5, 0), lane = threadIdx.x & 31;
    const int g = lane >> 2, t = lane & 3;
    unsigned char* const acc_g = acc_all + grp * ACC_GROUP;
    unsigned char* const score_p = acc_g + acc_line(16 + (lane >> 3)) + (lane & 7) * 16;

    if (elect()) {
#pragma unroll
        for (int i = 0; i < 4; i++) {
            const int u = (warp - 1) * 4 + i + 1;
            mbar_arm(bars + (B_FULL + u) * 8, (u & 19) == 19 || u == NSTAGE ? STAGE_B / 2 : STAGE_B);
            if (u < NSTAGE) mbar_init(bars + (B_FREE + u + 2) * 8, 12);
        }
        if (warp <= 4) {
            mbar_init(bars + (B_S + warp - 1) * 8, 4);
            mbar_init(bars + (B_P + warp - 1) * 8, 1);
            mbar_init(bars + (B_W + warp - 1) * 8, 4);
        } else if (warp < 8) {
            asm volatile("prefetch.tensormap [%0];" :: "l"(warp == 5 ? &emap : warp == 6 ? &fmap : &vmap) : "memory");
            mbar_arm(bars + (B_E + warp - 5) * 8, warp == 5 ? 4 * TILE_B + HPC * ROWB : (warp - 5) * 4 * TILE_B);
            mbar_arm(bars + (B_FULL + NSTAGE + warp - 4) * 8, 128 * SLICE_B);
        } else {
            asm volatile("prefetch.tensormap [%0];" :: "l"(&smap) : "memory");
            mbar_init(bars + (B_W + HPC) * 8, 8);
            mbar_init(bars + B_O * 8, 4);
            mbar_init(bars + B_T * 8, 1);
        }
    }
    __syncthreads();

    if (warp <= 4) {
        const int w = warp - 1;
        {
            const uint32_t tile = sb + OFF_EF + w * TILE_B;
            uint32_t ef[4][4][4];
            mbar_wait(bars + B_E * 8);
#pragma unroll
            for (int i = 0; i < 8; i++) {
                const uint4 ea = lds128(tile + (i * 8 + g) * 128 + (((2 * t) ^ g) << 4));
                const uint4 eb = lds128(tile + (i * 8 + g) * 128 + (((2 * t + 1) ^ g) << 4));
#pragma unroll
                for (int ks = 0; ks < 4; ks++) { ef[i >> 1][ks][i & 1] = word(ea, ks); ef[i >> 1][ks][2 + (i & 1)] = word(eb, ks); }
            }
            __syncwarp();
            if (lane == 0) mbar_arrive(bars + (B_FREE + (w < 2 ? 3 : 4)) * 8, w < 2 ? 6 : 4);

            const uint32_t kofs = sb + ((g & 3) * 16 + (g >> 2) * 8) * ROWB + t * 16 + (g & 1) * 64;
            const uint32_t qofs = sb + OFF_Q + t * 16 + (g & 1) * 4 + (g & 2) * 32;
            const uint32_t m0 = (g == t) ? 0xffffffffu : 0u, m1 = (g == t + 4) ? 0xffffffffu : 0u;
#pragma unroll 1
            for (int j = 0; j < HPC; j++) {
                const int s = j * 4 + w;
                uint32_t ka = kofs + (s % NS) * STAGE_B, qa = qofs + j * ROWB;
                mbar_wait(bars + (B_FULL + s) * 8);
                float d[8][4];
                zero(d);
#pragma unroll 1
                for (int i = 0; i < 3; i++, ka += 128, qa += 128) {
#pragma unroll
                    for (int h = 0; h < 2; h++) {
                        const uint32_t q0 = lds32(qa ^ (h * 64)), q1 = lds32((qa ^ (h * 64)) + 8);
#pragma unroll
                        for (int u = 0; u < 8; u++) {
                            const uint4 kv = lds128((ka ^ (h * 64)) + u * ROWB);
                            mma(d[u], kv.x, kv.y, kv.z, kv.w, q0, q1);
                        }
                    }
                }
                __syncwarp();
                if (lane == 0) mbar_arrive(bars + (B_FREE + s + NS) * 8, 12);

                float d2[4][4];
                zero(d2);
#pragma unroll
                for (int ks = 0; ks < 4; ks++) {
                    uint32_t hi, lo;
                    split2(d[2 * ks][0] + d[2 * ks][3], d[2 * ks + 1][0] + d[2 * ks + 1][3], hi, lo);
#pragma unroll
                    for (int i = 0; i < 4; i++) mma(d2[i], ef[i][ks][0], ef[i][ks][1], ef[i][ks][2], ef[i][ks][3], hi & m0, hi & m1);
#pragma unroll
                    for (int i = 0; i < 4; i++) mma(d2[i], ef[i][ks][0], ef[i][ks][1], ef[i][ks][2], ef[i][ks][3], lo & m0, lo & m1);
                }
                float x[4], y[4];
#pragma unroll
                for (int i = 0; i < 4; i++) { x[i] = d2[i][0] + d2[i][1]; y[i] = d2[i][2] + d2[i][3]; }
#pragma unroll
                for (int i = 0; i < 2; i++) {
                    x[i] = fsel(x[i], x[i + 2], t & 2) + __shfl_xor_sync(0xffffffffu, fsel(x[i + 2], x[i], t & 2), 2);
                    y[i] = fsel(y[i], y[i + 2], t & 2) + __shfl_xor_sync(0xffffffffu, fsel(y[i + 2], y[i], t & 2), 2);
                }
                const float sx = fsel(x[0], x[1], t & 1) + __shfl_xor_sync(0xffffffffu, fsel(x[1], x[0], t & 1), 1);
                const float sy = fsel(y[0], y[1], t & 1) + __shfl_xor_sync(0xffffffffu, fsel(y[1], y[0], t & 1), 1);
                sts32(sb + OFF_S + (j * 4 + w) * 256 + (16 * t + g) * 4, sx);
                sts32(sb + OFF_S + (j * 4 + w) * 256 + (16 * t + 8 + g) * 4, sy);
                __syncwarp();
                if (lane == 0) mbar_arrive(bars + (B_S + j) * 8);
                if (w == 3) {
                    mbar_wait(bars + (B_S + j) * 8);
                    const float2 p0 = lds64f(sb + OFF_S + (j * 4 + 0) * 256 + lane * 8);
                    const float2 p1 = lds64f(sb + OFF_S + (j * 4 + 1) * 256 + lane * 8);
                    const float2 p2 = lds64f(sb + OFF_S + (j * 4 + 2) * 256 + lane * 8);
                    const float2 p3 = lds64f(sb + OFF_S + (j * 4 + 3) * 256 + lane * 8);
                    contribute(score_p + j * ACC_SET, (p0.x + p1.x) + (p2.x + p3.x), (p0.y + p1.y) + (p2.y + p3.y));
                }
            }
        }

        const int mat = lane >> 3, mi = lane & 7;
        const uint32_t wofs = sb + OFF_W + (g & 1) * 64 + t * 16;
        {
            uint32_t off[3];
#pragma unroll
            for (int u = 0; u < 3; u++) {
                const int cc = w * 6 + u * 2 + (mat & 1), blk = cc >> 3;
                off[u] = sb + ((mat >> 1) * 8 + mi) * ROWB + blk * 128 + (((cc & 7) ^ ((3 * mi + blk) & 7)) << 4);
            }
            unsigned char* accp = acc_g + acc_line(w * 3 + t) + g * 16;
            float acc[3][4];
            auto rows32 = [&](uint32_t ofs, const uint4& wb) {
#pragma unroll
                for (int x = 0; x < 2; x++)
#pragma unroll
                    for (int u = 0; u < 3; u++) {
                        const uint4 a = ldsm4t(off[u] + ofs + x * 16 * ROWB);
                        mma(acc[u], a.x, a.y, a.z, a.w, word(wb, 2 * x), word(wb, 2 * x + 1));
                    }
            };
#pragma unroll 1
            for (int s = 16, slot = 16 % NS; s < NSTAGE; s++) {
                if ((s & 3) == 0) {
                    zero(acc);
                    mbar_wait(bars + (B_W - 4 + (s >> 2)) * 8);
                }
                const uint4 w0 = lds128(wofs + (s - 16) * 256), w1 = lds128(wofs + (s - 16) * 256 + 128);
                mbar_wait(bars + (B_FULL + s) * 8);
                rows32(slot * STAGE_B, w0);
                if ((s & 3) != 3) {
                    rows32(slot * STAGE_B + STAGE_B / 2, w1);
                } else {
                    const float x = fsel(fsel(acc[0][0] + acc[0][1], acc[1][0] + acc[1][1], t & 1), acc[2][0] + acc[2][1], t & 2);
                    const float y = fsel(fsel(acc[0][2] + acc[0][3], acc[1][2] + acc[1][3], t & 1), acc[2][2] + acc[2][3], t & 2);
                    if (t < 3) contribute(accp, x, y);
                    accp += ACC_SET;
                }
                __syncwarp();
                if (lane == 0 && s < 28) mbar_arrive(bars + (B_FREE + s + NS) * 8, 3);
                if (++slot == NS) slot = 0;
            }
            if (lane == 0) mbar_arrive(bars + B_O * 8);
        }

        if (w < 3) {
            uint32_t fa = sb + TAIL_SLOT * STAGE_B + ((mat >> 1) * 8 + mi) * SLICE_B + (2 * w + ((mat & 1) ^ (mi >> 2))) * 16;
            const int tcol = w * 16 + (t & 1) * 8 + g;
            const uint32_t tot_a = sb + OFF_T + (w * 8 + g) * 8 + (t & 1) * 4;
            __nv_bfloat16* outp = out + (grp + (c >> 2) * NG) * DH + (c & 3) * 48 + tcol;
            asm volatile("" : "+l"(outp));
            float acc[2][4];
            zero(acc);
            auto unit = [&](int i) {
                uint4 wb[4];
#pragma unroll
                for (int x = 0; x < 4; x++) wb[x] = lds128(wofs + HPC * 1024 + i * 512 + x * 128);
                mbar_wait(bars + (B_FULL + NSTAGE + i) * 8);
#pragma unroll
                for (int x = 0; x < 8; x++) {
                    const uint4 a = ldsm4t(fa + x * 16 * SLICE_B);
                    const bool sw = t >= 2;
                    mma(acc[x & 1], sw ? a.y : a.x, sw ? a.x : a.y, sw ? a.w : a.z, sw ? a.z : a.w,
                        word(wb[x >> 1], (x & 1) * 2), word(wb[x >> 1], (x & 1) * 2 + 1));
                }
                fa += 128 * SLICE_B;
            };
            mbar_wait(bars + (B_W + HPC) * 8);
#pragma unroll 1
            for (int i = 0; i < 3; i++) unit(i);
            auto store_if = [&](float o, uint32_t on) {
                asm volatile("{\n.reg .pred p;\n.reg .b16 h;\ncvt.rn.bf16.f32 h, %1;\nsetp.ne.u32 p, %2, 0;\n@p st.global.b16 [%0], h;\n}"
                             :: "l"(outp), "f"(o), "r"(on) : "memory");
            };
            const bool early = mbar_test(bars + B_T * 8);
            const float tot = early ? __uint_as_float(lds32(tot_a)) : 0.f;
            unit(3);
            const float o = (tot + fsel(acc[0][0] + acc[0][1], acc[0][2] + acc[0][3], t & 1)) +
                            fsel(acc[1][0] + acc[1][1], acc[1][2] + acc[1][3], t & 1);
            store_if(o, early && t < 2);
            if (!early) {
                mbar_wait(bars + B_T * 8);
                store_if(o + __uint_as_float(lds32(tot_a)), t < 2);
            }
        }
    } else {
        const int w = warp - 5;
        uint32_t fb[8][8];
#pragma unroll 1
        for (int j = 0; j < HPC + 2; j++) {
            if (j == 0 || j >= HPC) {
                const uint32_t tile = sb + (j == 0 ? OFF_EF + 4 * TILE_B : OFF_G + (j - HPC) * 4 * TILE_B) + w * TILE_B;
                mbar_wait(bars + (j == 0 ? B_F : B_G) * 8);
#pragma unroll
                for (int x = 0; x < 8; x++) {
                    const uint4 f0 = lds128(tile + (x * 8 + 2 * t) * 128 + ((g ^ (2 * t)) << 4));
                    const uint4 f1 = lds128(tile + (x * 8 + 2 * t + 1) * 128 + ((g ^ (2 * t + 1)) << 4));
#pragma unroll
                    for (int i = 0; i < 8; i++) fb[i][x] = __byte_perm(word(f0, i >> 1), word(f1, i >> 1), (i & 1) ? 0x7632 : 0x5410);
                }
                __syncwarp();
                if (j == 0 && lane == 0) mbar_arrive(bars + (B_FREE + (w == 0 ? 4 : 5)) * 8, 4);
            }
            if (j == w) {
                mbar_wait(bars + (B_FULL + READ_AT + 4 * j) * 8);
                float4 sc;
#pragma unroll 1
                for (int it = 0;; it++) {
                    sc = ld_relaxed16(score_p + j * ACC_SET);
                    if (__all_sync(0xffffffffu, sc.z == (float)NC)) break;
                    if (it > SPIN_LIMIT) __trap();
                    __nanosleep(500);
                }
                const float scale = 0.07216878364870322f;
                sc.x *= scale; sc.y *= scale;
                float m = fmaxf(sc.x, sc.y);
#pragma unroll
                for (int o = 16; o > 0; o >>= 1) m = fmaxf(m, __shfl_xor_sync(0xffffffffu, m, o));
                const float e0 = expf(sc.x - m), e1 = expf(sc.y - m);
                float sum = e0 + e1;
#pragma unroll
                for (int o = 16; o > 0; o >>= 1) sum += __shfl_xor_sync(0xffffffffu, sum, o);
                const float inv = 1.0f / sum;
                uint32_t hi, lo;
                split2(e0 * inv, e1 * inv, hi, lo);
                sts64(sb + OFF_P + j * 256 + (g >> 1) * 64 + t * 16 + (g & 1) * 8, hi, lo);
                __syncwarp();
                if (lane == 0) mbar_arrive(bars + (B_P + j) * 8);
            }
            const int pj = j < HPC ? j : c >> 2;
            mbar_wait(bars + (B_P + pj) * 8);
            float d[8][4];
            zero(d);
#pragma unroll
            for (int ks = 0; ks < 4; ks++) {
                const uint4 a = lds128(sb + OFF_P + pj * 256 + ks * 64 + t * 16);
#pragma unroll
                for (int i = 0; i < 8; i++) mma(d[i], a.x, a.y, a.z, a.w, fb[i][2 * ks], fb[i][2 * ks + 1]);
            }
            float x[8], y[8];
#pragma unroll
            for (int i = 0; i < 8; i++) { x[i] = d[i][0] + d[i][2]; y[i] = d[i][1] + d[i][3]; }
#pragma unroll
            for (int i = 0; i < 4; i++) { x[i] = fsel(x[i], x[i + 4], g & 4); y[i] = fsel(y[i], y[i + 4], g & 4); }
#pragma unroll
            for (int i = 0; i < 2; i++) { x[i] = fsel(x[i], x[i + 2], g & 2); y[i] = fsel(y[i], y[i + 2], g & 2); }
            uint32_t xh, xl, yh, yl;
            split2(x[0], x[1], xh, xl);
            split2(y[0], y[1], yh, yl);
            sts64(sb + OFF_W + (j * 4 + w) * 256 + (t >> 1) * 128 + (g & 1) * 64 + (g >> 1) * 16 + (t & 1) * 8,
                  (g & 1) ? xl : xh, (g & 1) ? yl : yh);
            __syncwarp();
            if (lane == 0) mbar_arrive(bars + (B_W + min(j, HPC)) * 8);
        }
        if (w == 3) {
            unsigned char* tp = acc_g + (c >> 2) * ACC_SET + acc_line(lane < 24 ? (c & 3) * 3 + (lane >> 3) : 16 + (c & 3)) + (lane & 7) * 16;
            mbar_wait(bars + (c < 12 ? B_FULL + 30 : B_O) * 8);
            __nanosleep(POLL_LAG_NS);
            float4 r;
#pragma unroll 1
            for (int it = 0;; it++) {
                if (lane < 24) r = ld_relaxed16(tp);
                if (__all_sync(0xffffffffu, lane >= 24 || r.z == (float)NC)) break;
                if (it > SPIN_LIMIT) __trap();
            }
            if (lane < 24) sts64(sb + OFF_T + lane * 8, __float_as_uint(r.x), __float_as_uint(r.y));
            __syncwarp();
            if (lane == 0) mbar_arrive(bars + B_T * 8);
            asm volatile("st.global.v4.u32 [%0], {%1,%1,%1,%1};" :: "l"(tp), "r"(0) : "memory");
        }
    }
}

static CUtensorMap make_map(const void* p, uint64_t cols, uint64_t rows, uint32_t box_cols, uint32_t box_rows) {
    typedef CUresult (*EncodeFn)(CUtensorMap*, CUtensorMapDataType, cuuint32_t, void*, const cuuint64_t*, const cuuint64_t*,
                                 const cuuint32_t*, const cuuint32_t*, CUtensorMapInterleave, CUtensorMapSwizzle,
                                 CUtensorMapL2promotion, CUtensorMapFloatOOBfill);
    void* fn = nullptr;
    cudaDriverEntryPointQueryResult qr;
    cudaGetDriverEntryPoint("cuTensorMapEncodeTiled", &fn, cudaEnableDefault, &qr);
    CUtensorMap m;
    const cuuint64_t dims[2] = {cols, rows};
    const cuuint64_t strides[1] = {cols * 2};
    const cuuint32_t box[2] = {box_cols, box_rows};
    const cuuint32_t estr[2] = {1, 1};
    ((EncodeFn)fn)(&m, CU_TENSOR_MAP_DATA_TYPE_BFLOAT16, 2, (void*)p, dims, strides, box, estr, CU_TENSOR_MAP_INTERLEAVE_NONE,
                   box_cols == 64 ? CU_TENSOR_MAP_SWIZZLE_128B : CU_TENSOR_MAP_SWIZZLE_NONE,
                   box_cols == 64 ? CU_TENSOR_MAP_L2_PROMOTION_NONE : CU_TENSOR_MAP_L2_PROMOTION_L2_128B,
                   CU_TENSOR_MAP_FLOAT_OOB_FILL_NONE);
    return m;
}

}

extern "C" void kernel_launch(void* const* d_in, const int* in_sizes, int n_in, void* d_out, int out_size) {
    using namespace lf;
    void* acc = nullptr;
    cudaGetSymbolAddress(&acc, g_acc);
    acc = (void*)(((uintptr_t)acc + ACC_GROUP - 1) & ~(uintptr_t)(ACC_GROUP - 1));
    cudaFuncSetAttribute(linformer_decode_kernel, cudaFuncAttributeMaxDynamicSharedMemorySize, SMEM_BYTES);
    int dev = 0, mem_khz = 0, bus_bits = 0;
    cudaGetDevice(&dev);
    cudaDeviceGetAttribute(&mem_khz, cudaDevAttrMemoryClockRate, dev);
    cudaDeviceGetAttribute(&bus_bits, cudaDevAttrGlobalMemoryBusWidth, dev);
    const double bytes_per_ns = 0.9775 * 2e-6 * mem_khz * (bus_bits / 8);
    const int period_ns = bytes_per_ns > 1.0 ? (int)(NCTA * STAGE_B / bytes_per_ns) : 0;
    cudaLaunchAttribute attr;
    attr.id = cudaLaunchAttributeCooperative;
    attr.val.cooperative = 1;
    cudaLaunchConfig_t cfg = {};
    cfg.gridDim = dim3(NCTA);
    cfg.blockDim = dim3(NWARPS * 32);
    cfg.dynamicSmemBytes = SMEM_BYTES;
    cfg.stream = cudaStreamPerThread;
    cfg.attrs = &attr;
    cfg.numAttrs = 1;
    cudaLaunchKernelEx(&cfg, linformer_decode_kernel,
                       (const __nv_bfloat16*)d_in[1], (const __nv_bfloat16*)d_in[0], (__nv_bfloat16*)d_out, (unsigned char*)acc, period_ns,
                       make_map(d_in[2], 64, (uint64_t)H * SKV * 3, 64, 96),
                       make_map(d_in[2], DH, (uint64_t)H * SKV, 48, 128),
                       make_map(d_in[3], SKV, 64, 64, 64), make_map(d_in[4], SKV, 64, 64, 64));
}
```

```cpp
#include <cuda.h>
#include <cuda_runtime.h>
#include <cuda_bf16.h>
#include <stdint.h>

namespace lf {

constexpr int H = 32, SKV = 4096, DH = 192;
constexpr int NCTA = 128;
constexpr int NC = 16;
constexpr int NG = 8;
constexpr int HPC = 4;
constexpr int ROWB = DH * 2;
constexpr int STAGE_B = 64 * ROWB;
constexpr int NS = 6;
constexpr int NSTAGE = 32;
constexpr int TAIL_ROW = SKV - 512;
constexpr int NWARPS = 9;

constexpr int FLY_START = 3, FLY_MIN = 2, FLY_MAX = 5;
constexpr int LEAD_NS = 770;
constexpr int POLL_LAG_NS = 200;
constexpr int READ_AT = 8;

constexpr int TILE_B = 64 * 128;
constexpr int OFF_G = NS * STAGE_B;
constexpr int OFF_W = OFF_G + 8 * TILE_B;
constexpr int OFF_P = OFF_W + 6144;
constexpr int OFF_S = OFF_P + 1024;
constexpr int OFF_Q = OFF_S + 4096;
constexpr int OFF_T = OFF_Q + 1536;
constexpr int OFF_T0 = OFF_T + 192;
constexpr int OFF_BAR = OFF_T0 + 8;
constexpr int B_FULL = 0, B_FREE = NSTAGE - NS, B_S = 58, B_P = 62, B_W = 66, B_O = 71, B_T = 72, B_Q = 73, B_TF = 74, B_TE = 98;
constexpr int SMEM_BYTES = OFF_BAR + 106 * 8;

constexpr int SPIN_LIMIT = 1 << 20;

constexpr int ACC_GROUP = 65536, ACC_SET = 4096;
__device__ unsigned char g_acc[(NG + 1) * ACC_GROUP];
__device__ __forceinline__ int acc_line(int i) { return (i & 1) * 256 + ((i >> 1) & 3) * 1024 + (i >> 3) * 16384; }

__device__ __forceinline__ uint32_t smem_u32(const void* p) { return (uint32_t)__cvta_generic_to_shared(p); }
__device__ __forceinline__ void mbar_init(uint32_t bar, uint32_t cnt) {
    asm volatile("mbarrier.init.shared::cta.b64 [%0], %1;" :: "r"(bar), "r"(cnt) : "memory");
}
__device__ __forceinline__ void mbar_arm(uint32_t bar, uint32_t bytes) {
    mbar_init(bar, 1);
    asm volatile("mbarrier.arrive.expect_tx.shared::cta.b64 _, [%0], %1;" :: "r"(bar), "r"(bytes) : "memory");
}
__device__ __forceinline__ void mbar_arrive(uint32_t bar, uint32_t n = 1) {
    asm volatile("mbarrier.arrive.shared::cta.b64 _, [%0], %1;" :: "r"(bar), "r"(n) : "memory");
}
__device__ __forceinline__ bool mbar_test(uint32_t bar) {
    uint32_t ok;
    asm volatile("{\n.reg .pred p;\nmbarrier.test_wait.parity.shared::cta.b64 p, [%1], 0;\nselp.u32 %0, 1, 0, p;\n}"
                 : "=r"(ok) : "r"(bar) : "memory");
    return ok;
}
__device__ __forceinline__ void mbar_wait(uint32_t bar) {
    asm volatile("{\n.reg .pred p, q;\n.reg .u32 n;\nmov.u32 n, 0;\n"
                 "LF_WAIT_%=:\n"
                 "mbarrier.try_wait.parity.shared::cta.b64 p, [%0], 0;\n"
                 "add.u32 n, n, 1;\n"
                 "setp.lt.u32 q, n, %1;\n"
                 "and.pred q, q, !p;\n"
                 "@q bra LF_WAIT_%=;\n}"
                 :: "r"(bar), "n"(SPIN_LIMIT) : "memory");
}
__device__ __forceinline__ uint64_t evict_first() {
    uint64_t pol;
    asm("createpolicy.fractional.L2::evict_first.b64 %0, 1.0;" : "=l"(pol));
    return pol;
}
__device__ __forceinline__ void bulk_g2s(uint32_t dst, const void* src, uint32_t bytes, uint32_t bar) {
    asm volatile("cp.async.bulk.shared::cluster.global.mbarrier::complete_tx::bytes.L2::cache_hint [%0], [%1], %2, [%3], %4;"
                 :: "r"(dst), "l"(src), "r"(bytes), "r"(bar), "l"(evict_first()) : "memory");
}
__device__ __forceinline__ void tile_g2s(uint32_t dst, const CUtensorMap* map, int x, int y, uint32_t bar) {
    asm volatile("cp.async.bulk.tensor.2d.shared::cluster.global.mbarrier::complete_tx::bytes [%0], [%1, {%2, %3}], [%4];"
                 :: "r"(dst), "l"(map), "r"(x), "r"(y), "r"(bar) : "memory");
}
__device__ __forceinline__ void lines_g2s(uint32_t dst, const CUtensorMap* map, int line0, uint32_t bar) {
    asm volatile("cp.async.bulk.tensor.2d.shared::cluster.global.mbarrier::complete_tx::bytes.L2::cache_hint [%0], [%1, {%2, %3}], [%4], %5;"
                 :: "r"(dst), "l"(map), "r"(0), "r"(line0), "r"(bar), "l"(evict_first()) : "memory");
}
__device__ __forceinline__ uint32_t now_ns() {
    uint32_t t;
    asm volatile("mov.u32 %0, %globaltimer_lo;" : "=r"(t));
    return t;
}
__device__ __forceinline__ bool elect() {
    uint32_t p;
    asm volatile("{\n.reg .pred P;\nelect.sync _|P, 0xffffffff;\nselp.u32 %0, 1, 0, P;\n}" : "=r"(p));
    return p;
}
__device__ __forceinline__ void mma(float (&d)[4], uint32_t a0, uint32_t a1, uint32_t a2, uint32_t a3, uint32_t b0, uint32_t b1) {
    asm volatile("mma.sync.aligned.m16n8k16.row.col.f32.bf16.bf16.f32 {%0,%1,%2,%3}, {%4,%5,%6,%7}, {%8,%9}, {%0,%1,%2,%3};"
                 : "+f"(d[0]), "+f"(d[1]), "+f"(d[2]), "+f"(d[3])
                 : "r"(a0), "r"(a1), "r"(a2), "r"(a3), "r"(b0), "r"(b1));
}
template <int N>
__device__ __forceinline__ void zero(float (&d)[N][4]) {
#pragma unroll
    for (int i = 0; i < N; i++) d[i][0] = d[i][1] = d[i][2] = d[i][3] = 0.f;
}
__device__ __forceinline__ uint4 lds128(uint32_t addr) {
    uint4 v;
    asm volatile("ld.shared.v4.u32 {%0,%1,%2,%3}, [%4];" : "=r"(v.x), "=r"(v.y), "=r"(v.z), "=r"(v.w) : "r"(addr) : "memory");
    return v;
}
__device__ __forceinline__ float2 lds64f(uint32_t addr) {
    float2 v;
    asm volatile("ld.shared.v2.f32 {%0,%1}, [%2];" : "=f"(v.x), "=f"(v.y) : "r"(addr) : "memory");
    return v;
}
__device__ __forceinline__ uint32_t lds32(uint32_t addr) {
    uint32_t v;
    asm volatile("ld.shared.u32 %0, [%1];" : "=r"(v) : "r"(addr) : "memory");
    return v;
}
__device__ __forceinline__ void sts64(uint32_t addr, uint32_t x, uint32_t y) {
    asm volatile("st.shared.v2.u32 [%0], {%1,%2};" :: "r"(addr), "r"(x), "r"(y) : "memory");
}
__device__ __forceinline__ void sts32(uint32_t addr, float x) {
    asm volatile("st.shared.f32 [%0], %1;" :: "r"(addr), "f"(x) : "memory");
}
__device__ __forceinline__ uint4 ldsm4t(uint32_t addr) {
    uint4 v;
    asm volatile("ldmatrix.sync.aligned.m8n8.x4.trans.shared.b16 {%0,%1,%2,%3}, [%4];"
                 : "=r"(v.x), "=r"(v.y), "=r"(v.z), "=r"(v.w) : "r"(addr) : "memory");
    return v;
}
__device__ __forceinline__ float fsel(float a, float b, uint32_t pick_b) {
    float r;
    asm("{\n.reg .pred s;\nsetp.ne.u32 s, %3, 0;\nselp.f32 %0, %2, %1, s;\n}" : "=f"(r) : "f"(a), "f"(b), "r"(pick_b));
    return r;
}
__device__ __forceinline__ uint32_t pack_bf16(float x, float y) {
    uint32_t r;
    asm("cvt.rn.bf16x2.f32 %0, %1, %2;" : "=r"(r) : "f"(y), "f"(x));
    return r;
}
__device__ __forceinline__ void split2(float x, float y, uint32_t& hi, uint32_t& lo) {
    hi = pack_bf16(x, y);
    lo = pack_bf16(x - __uint_as_float(hi << 16), y - __uint_as_float(hi & 0xffff0000u));
}
__device__ __forceinline__ uint32_t word(const uint4& v, int i) { return i == 0 ? v.x : i == 1 ? v.y : i == 2 ? v.z : v.w; }

__device__ __forceinline__ void contribute(void* p, float x, float y) {
    asm volatile("red.relaxed.gpu.global.add.v4.f32 [%0], {%1,%2,%3,%4};" :: "l"(p), "f"(x), "f"(y), "f"(1.f), "f"(0.f) : "memory");
}
__device__ __forceinline__ float4 ld_relaxed16(const void* p) {
    float4 r;
    asm volatile("{\n.reg .b128 u;\n.reg .b64 a, b;\nld.relaxed.gpu.global.b128 u, [%4];\nmov.b128 {a, b}, u;\n"
                 "mov.b64 {%0, %1}, a;\nmov.b64 {%2, %3}, b;\n}"
                 : "=f"(r.x), "=f"(r.y), "=f"(r.z), "=f"(r.w) : "l"(p) : "memory");
    return r;
}

__global__ void __launch_bounds__(NWARPS * 32, 1)
linformer_decode_kernel(const __nv_bfloat16* __restrict__ k, const __nv_bfloat16* __restrict__ q,
                        __nv_bfloat16* __restrict__ out, unsigned char* __restrict__ acc_all, int period_ns,
                        const __grid_constant__ CUtensorMap vmap, const __grid_constant__ CUtensorMap smap,
                        const __grid_constant__ CUtensorMap emap, const __grid_constant__ CUtensorMap fmap) {
    extern __shared__ __align__(1024) unsigned char smem[];
    const uint32_t sb = smem_u32(smem);
    const uint32_t bars = sb + OFF_BAR;
    const int grp = blockIdx.x >> 4, c = blockIdx.x & (NC - 1);

    asm volatile("prefetch.global.L2 [%0];" :: "l"((const char*)k + (uint32_t)(((grp * 64 + c) * (STAGE_B / 64) + threadIdx.x) * 64)) : "memory");
    if (threadIdx.x < 32) {
        const bool leader = elect();
        auto issue_k = [&](int s, int slot) {
            const int row = (grp + (s >> 2) * NG) * SKV + (s & 3) * 1024 + c * 64;
            bulk_g2s(sb + slot * STAGE_B, (const char*)k + (size_t)row * ROWB, STAGE_B, bars + (B_FULL + s) * 8);
        };
        if (leader) {
            mbar_arm(bars + B_FULL * 8, STAGE_B);
            issue_k(0, 0);
            sts32(sb + OFF_T0, __uint_as_float(now_ns()));
        }
        __syncthreads();
        if (leader) {
            auto issue_tile = [&](int i) {
                if (i >= 8) mbar_wait(bars + (B_TE - 8 + i) * 8);
                const int x = i >= 8 ? TAIL_ROW + (i - 8) * 64 : (i & 3) * 1024 + c * (i == 7 ? 32 : 64);
                tile_g2s(sb + OFF_G + (i & 7) * TILE_B, i < 4 ? &emap : &fmap, x, 0, bars + (B_TF + i) * 8);
            };
#pragma unroll
            for (int j = 0; j < HPC; j++) bulk_g2s(sb + OFF_Q + j * ROWB, q + (j * NG + grp) * DH, ROWB, bars + B_Q * 8);
            issue_tile(0);
#pragma unroll
            for (int s = 1; s < FLY_START; s++) { issue_k(s, s); issue_tile(s); }

            uint32_t fly = (1u << FLY_START) - 1, scan = fly;
            const int tile_ns = period_ns / 24;
            uint32_t due = lds32(sb + OFF_T0) + FLY_START * (period_ns + tile_ns) - LEAD_NS;
#pragma unroll 1
            for (int s = FLY_START, slot = FLY_START, it = 0; it < SPIN_LIMIT * 64; it++) {
                const int late = (int)(now_ns() - due);
                if (__popc(fly) < (late <= 0 ? FLY_MIN : s < NSTAGE ? FLY_MAX : NSTAGE)) {
                    if (s == NSTAGE) {
                        due += min(late, 0);
                        break;
                    }
                    if (s >= NS) mbar_wait(bars + (B_FREE + s) * 8);
                    if (s < 16) {
                        issue_k(s, slot);
                        issue_tile(s);
                        due += period_ns + (s < 8 ? tile_ns : 0);
                    } else {
                        const bool full = (s & 3) != 3;
                        const int line = ((grp + ((s >> 2) & 3) * NG) * SKV + (s & 3) * 1024 + c * (full ? 64 : 32)) * 3;
                        lines_g2s(sb + slot * STAGE_B, &vmap, line, bars + (B_FULL + s) * 8);
                        if (full) lines_g2s(sb + slot * STAGE_B + STAGE_B / 2, &vmap, line + 96, bars + (B_FULL + s) * 8);
                        due += full ? period_ns : period_ns / 2;
                        if (s == NSTAGE - 1) mbar_wait(bars + (B_W + HPC) * 8);
                    }
                    fly |= 1u << s;
                    s++;
                    if (++slot == NS) slot = 0;
                } else {
                    if (!scan) scan = fly;
                    const int m = __ffs(scan) - 1;
                    scan &= scan - 1;
                    if (mbar_test(bars + (B_FULL + m) * 8)) fly ^= 1u << m;
                }
            }
            const int row = (grp + (c >> 2) * NG) * SKV + TAIL_ROW, step_ns = period_ns * 7 / 48;
#pragma unroll 1
            for (int i = 0; i < 16; i++, due += step_ns) {
#pragma unroll 1
                for (int it = 0; (int)(now_ns() - due) < 0 && it < SPIN_LIMIT; it++) {}
                tile_g2s(sb + OFF_G + i * (TILE_B / 2), &smap, (c & 3) * 48, row + i * 32, bars + (B_TF + 16 + (i >> 1)) * 8);
            }
        }
        return;
    }

    const int warp = __shfl_sync(0xffffffffu, threadIdx.x >> 5, 0), lane = threadIdx.x & 31;
    const int g = lane >> 2, t = lane & 3;
    unsigned char* const acc_g = acc_all + grp * ACC_GROUP;
    unsigned char* const score_p = acc_g + acc_line(16 + (lane >> 3)) + (lane & 7) * 16;

    if (elect()) {
#pragma unroll
        for (int i = 0; i < 4; i++) {
            const int s = (warp - 1) * 4 + i;
            if (s > 0) mbar_arm(bars + (B_FULL + s) * 8, (s & 19) == 19 ? STAGE_B / 2 : STAGE_B);
            if (s >= NS) mbar_init(bars + (B_FREE + s) * 8, 4);
            if (i < 3) mbar_arm(bars + (B_TF + i * 8 + warp - 1) * 8, TILE_B);
        }
        mbar_init(bars + (B_TE + warp - 1) * 8, 1);
        if (warp <= 4) {
            mbar_init(bars + (B_S + warp - 1) * 8, 4);
            mbar_init(bars + (B_P + warp - 1) * 8, 1);
            mbar_init(bars + (B_W + warp - 1) * 8, 4);
        } else {
            asm volatile("prefetch.tensormap [%0];" :: "l"(warp == 5 ? &emap : warp == 6 ? &fmap : warp == 7 ? &vmap : &smap) : "memory");
            if (warp == 5) mbar_arm(bars + B_Q * 8, HPC * ROWB);
            else mbar_init(bars + (B_W + HPC + warp - 6) * 8, warp == 6 ? 8 : warp == 7 ? 4 : 1);
        }
    }
    __syncthreads();

    if (warp <= 4) {
        const int w = warp - 1;
        {
            const uint32_t tile = sb + OFF_G + w * TILE_B;
            uint32_t ef[4][4][4];
            mbar_wait(bars + B_Q * 8);

            const uint32_t kofs = sb + ((g & 3) * 16 + (g >> 2) * 8) * ROWB + t * 16 + (g & 1) * 64;
            const uint32_t qofs = sb + OFF_Q + t * 16 + (g & 1) * 4 + (g & 2) * 32;
            const uint32_t m0 = (g == t) ? 0xffffffffu : 0u, m1 = (g == t + 4) ? 0xffffffffu : 0u;
#pragma unroll 1
            for (int j = 0; j < HPC; j++) {
                const int s = j * 4 + w;
                uint32_t ka = kofs + (s % NS) * STAGE_B, qa = qofs + j * ROWB;
                mbar_wait(bars + (B_FULL + s) * 8);
                float d[8][4];
                zero(d);
#pragma unroll 1
                for (int i = 0; i < 3; i++, ka += 128, qa += 128) {
#pragma unroll
                    for (int h = 0; h < 2; h++) {
                        const uint32_t q0 = lds32(qa ^ (h * 64)), q1 = lds32((qa ^ (h * 64)) + 8);
#pragma unroll
                        for (int u = 0; u < 8; u++) {
                            const uint4 kv = lds128((ka ^ (h * 64)) + u * ROWB);
                            mma(d[u], kv.x, kv.y, kv.z, kv.w, q0, q1);
                        }
                    }
                }
                __syncwarp();
                if (lane == 0) mbar_arrive(bars + (B_FREE + s + NS) * 8, 4);

                if (j == 0) {
                    mbar_wait(bars + (B_TF + w) * 8);
#pragma unroll
                    for (int i = 0; i < 8; i++) {
                        const uint4 ea = lds128(tile + (i * 8 + g) * 128 + (((2 * t) ^ g) << 4));
                        const uint4 eb = lds128(tile + (i * 8 + g) * 128 + (((2 * t + 1) ^ g) << 4));
#pragma unroll
                        for (int ks = 0; ks < 4; ks++) { ef[i >> 1][ks][i & 1] = word(ea, ks); ef[i >> 1][ks][2 + (i & 1)] = word(eb, ks); }
                    }
                    __syncwarp();
                    if (lane == 0) mbar_arrive(bars + (B_TE + w) * 8);
                }
                float d2[4][4];
                zero(d2);
#pragma unroll
                for (int ks = 0; ks < 4; ks++) {
                    uint32_t hi, lo;
                    split2(d[2 * ks][0] + d[2 * ks][3], d[2 * ks + 1][0] + d[2 * ks + 1][3], hi, lo);
#pragma unroll
                    for (int i = 0; i < 4; i++) mma(d2[i], ef[i][ks][0], ef[i][ks][1], ef[i][ks][2], ef[i][ks][3], hi & m0, hi & m1);
#pragma unroll
                    for (int i = 0; i < 4; i++) mma(d2[i], ef[i][ks][0], ef[i][ks][1], ef[i][ks][2], ef[i][ks][3], lo & m0, lo & m1);
                }
                float x[4], y[4];
#pragma unroll
                for (int i = 0; i < 4; i++) { x[i] = d2[i][0] + d2[i][1]; y[i] = d2[i][2] + d2[i][3]; }
#pragma unroll
                for (int i = 0; i < 2; i++) {
                    x[i] = fsel(x[i], x[i + 2], t & 2) + __shfl_xor_sync(0xffffffffu, fsel(x[i + 2], x[i], t & 2), 2);
                    y[i] = fsel(y[i], y[i + 2], t & 2) + __shfl_xor_sync(0xffffffffu, fsel(y[i + 2], y[i], t & 2), 2);
                }
                const float sx = fsel(x[0], x[1], t & 1) + __shfl_xor_sync(0xffffffffu, fsel(x[1], x[0], t & 1), 1);
                const float sy = fsel(y[0], y[1], t & 1) + __shfl_xor_sync(0xffffffffu, fsel(y[1], y[0], t & 1), 1);
                sts32(sb + OFF_S + (j * 4 + w) * 256 + (16 * t + g) * 4, sx);
                sts32(sb + OFF_S + (j * 4 + w) * 256 + (16 * t + 8 + g) * 4, sy);
                __syncwarp();
                if (lane == 0) mbar_arrive(bars + (B_S + j) * 8);
                if (w == 3) {
                    mbar_wait(bars + (B_S + j) * 8);
                    const float2 p0 = lds64f(sb + OFF_S + (j * 4 + 0) * 256 + lane * 8);
                    const float2 p1 = lds64f(sb + OFF_S + (j * 4 + 1) * 256 + lane * 8);
                    const float2 p2 = lds64f(sb + OFF_S + (j * 4 + 2) * 256 + lane * 8);
                    const float2 p3 = lds64f(sb + OFF_S + (j * 4 + 3) * 256 + lane * 8);
                    contribute(score_p + j * ACC_SET, (p0.x + p1.x) + (p2.x + p3.x), (p0.y + p1.y) + (p2.y + p3.y));
                }
            }
        }

        const int mat = lane >> 3, mi = lane & 7;
        const uint32_t wofs = sb + OFF_W + (g & 1) * 64 + t * 16;
        {
            uint32_t off[3];
#pragma unroll
            for (int u = 0; u < 3; u++) {
                const int cc = w * 6 + u * 2 + (mat & 1), blk = cc >> 3;
                off[u] = sb + ((mat >> 1) * 8 + mi) * ROWB + blk * 128 + (((cc & 7) ^ ((3 * mi + blk) & 7)) << 4);
            }
            unsigned char* accp = acc_g + acc_line(w * 3 + t) + g * 16;
            float acc[3][4];
            auto rows32 = [&](uint32_t ofs, const uint4& wb) {
#pragma unroll
                for (int x = 0; x < 2; x++)
#pragma unroll
                    for (int u = 0; u < 3; u++) {
                        const uint4 a = ldsm4t(off[u] + ofs + x * 16 * ROWB);
                        mma(acc[u], a.x, a.y, a.z, a.w, word(wb, 2 * x), word(wb, 2 * x + 1));
                    }
            };
#pragma unroll 1
            for (int s = 16, slot = 16 % NS; s < NSTAGE; s++) {
                if ((s & 3) == 0) {
                    zero(acc);
                    mbar_wait(bars + (B_W - 4 + (s >> 2)) * 8);
                }
                const uint4 w0 = lds128(wofs + (s - 16) * 256), w1 = lds128(wofs + (s - 16) * 256 + 128);
                mbar_wait(bars + (B_FULL + s) * 8);
                rows32(slot * STAGE_B, w0);
                if ((s & 3) != 3) {
                    rows32(slot * STAGE_B + STAGE_B / 2, w1);
                } else {
                    const float x = fsel(fsel(acc[0][0] + acc[0][1], acc[1][0] + acc[1][1], t & 1), acc[2][0] + acc[2][1], t & 2);
                    const float y = fsel(fsel(acc[0][2] + acc[0][3], acc[1][2] + acc[1][3], t & 1), acc[2][2] + acc[2][3], t & 2);
                    if (t < 3) contribute(accp, x, y);
                    accp += ACC_SET;
                }
                __syncwarp();
                if (lane == 0 && s < NSTAGE - NS) mbar_arrive(bars + (B_FREE + s + NS) * 8);
                if (++slot == NS) slot = 0;
            }
            if (lane == 0) mbar_arrive(bars + B_O * 8);
        }

        if (w < 3) {
            uint32_t fa = sb + OFF_G + ((mat >> 1) * 8 + mi) * 128 + (((2 * w + (mat & 1)) ^ mi) << 4);
            const uint32_t tot_a = sb + OFF_T + (w * 8 + g) * 8 + (t & 1) * 4;
            __nv_bfloat16* outp = out + (grp + (c >> 2) * NG) * DH + (c & 3) * 48 + w * 16 + (t & 1) * 8 + g;
            asm volatile("" : "+l"(outp));
            float acc[4][4];
            zero(acc);
            mbar_wait(bars + (B_W + HPC) * 8);
            uint4 wb[16];
#pragma unroll
            for (int x = 0; x < 16; x++) wb[x] = lds128(wofs + HPC * 1024 + x * 128);
            auto rows64 = [&](int i) {
                mbar_wait(bars + (B_TF + 16 + i) * 8);
#pragma unroll
                for (int x = 0; x < 4; x++) {
                    const uint4 a = ldsm4t(fa + i * TILE_B + x * 16 * 128);
                    mma(acc[x], a.x, a.y, a.z, a.w, word(wb[2 * i + (x >> 1)], (x & 1) * 2), word(wb[2 * i + (x >> 1)], (x & 1) * 2 + 1));
                }
            };
#pragma unroll
            for (int i = 0; i < 7; i++) rows64(i);
            auto store_if = [&](float o, uint32_t on) {
                asm volatile("{\n.reg .pred p;\n.reg .b16 h;\ncvt.rn.bf16.f32 h, %1;\nsetp.ne.u32 p, %2, 0;\n@p st.global.b16 [%0], h;\n}"
                             :: "l"(outp), "f"(o), "r"(on) : "memory");
            };
            const bool early = mbar_test(bars + B_T * 8);
            float o = early ? __uint_as_float(lds32(tot_a)) : 0.f;
            rows64(7);
#pragma unroll
            for (int i = 0; i < 4; i++) o += fsel(acc[i][0] + acc[i][1], acc[i][2] + acc[i][3], t & 1);
            store_if(o, early && t < 2);
            if (!early) {
                mbar_wait(bars + B_T * 8);
                store_if(o + __uint_as_float(lds32(tot_a)), t < 2);
            }
        }
    } else {
        const int w = warp - 5;
        uint32_t fb[8][8];
#pragma unroll 1
        for (int j = 0; j < HPC + 2; j++) {
            if (j == 0 || j >= HPC) {
                const int ti = (j == 0 ? 4 : (j - 2) * 4) + w;
                const uint32_t tile = sb + OFF_G + (ti & 7) * TILE_B;
                mbar_wait(bars + (B_TF + ti) * 8);
#pragma unroll
                for (int x = 0; x < 8; x++) {
                    const uint4 f0 = lds128(tile + (x * 8 + 2 * t) * 128 + ((g ^ (2 * t)) << 4));
                    const uint4 f1 = lds128(tile + (x * 8 + 2 * t + 1) * 128 + ((g ^ (2 * t + 1)) << 4));
#pragma unroll
                    for (int i = 0; i < 8; i++) fb[i][x] = __byte_perm(word(f0, i >> 1), word(f1, i >> 1), (i & 1) ? 0x7632 : 0x5410);
                }
                __syncwarp();
                if (j == 0 && lane == 0) mbar_arrive(bars + (B_TE + 4 + w) * 8);
            }
            if (j == w) {
                mbar_wait(bars + (B_FULL + READ_AT + 4 * j) * 8);
                float4 sc;
#pragma unroll 1
                for (int it = 0;; it++) {
                    sc = ld_relaxed16(score_p + j * ACC_SET);
                    if (__all_sync(0xffffffffu, sc.z == (float)NC)) break;
                    if (it > SPIN_LIMIT) __trap();
                    __nanosleep(500);
                }
                const float scale = 0.07216878364870322f;
                sc.x *= scale; sc.y *= scale;
                float m = fmaxf(sc.x, sc.y);
#pragma unroll
                for (int o = 16; o > 0; o >>= 1) m = fmaxf(m, __shfl_xor_sync(0xffffffffu, m, o));
                const float e0 = expf(sc.x - m), e1 = expf(sc.y - m);
                float sum = e0 + e1;
#pragma unroll
                for (int o = 16; o > 0; o >>= 1) sum += __shfl_xor_sync(0xffffffffu, sum, o);
                const float inv = 1.0f / sum;
                uint32_t hi, lo;
                split2(e0 * inv, e1 * inv, hi, lo);
                sts64(sb + OFF_P + j * 256 + (g >> 1) * 64 + t * 16 + (g & 1) * 8, hi, lo);
                __syncwarp();
                if (lane == 0) mbar_arrive(bars + (B_P + j) * 8);
            }
            const int pj = j < HPC ? j : c >> 2;
            mbar_wait(bars + (B_P + pj) * 8);
            float d[8][4];
            zero(d);
#pragma unroll
            for (int ks = 0; ks < 4; ks++) {
                const uint4 a = lds128(sb + OFF_P + pj * 256 + ks * 64 + t * 16);
#pragma unroll
                for (int i = 0; i < 8; i++) mma(d[i], a.x, a.y, a.z, a.w, fb[i][2 * ks], fb[i][2 * ks + 1]);
            }
            float x[8], y[8];
#pragma unroll
            for (int i = 0; i < 8; i++) { x[i] = d[i][0] + d[i][2]; y[i] = d[i][1] + d[i][3]; }
#pragma unroll
            for (int i = 0; i < 4; i++) { x[i] = fsel(x[i], x[i + 4], g & 4); y[i] = fsel(y[i], y[i + 4], g & 4); }
#pragma unroll
            for (int i = 0; i < 2; i++) { x[i] = fsel(x[i], x[i + 2], g & 2); y[i] = fsel(y[i], y[i + 2], g & 2); }
            uint32_t xh, xl, yh, yl;
            split2(x[0], x[1], xh, xl);
            split2(y[0], y[1], yh, yl);
            sts64(sb + OFF_W + (j * 4 + w) * 256 + (t >> 1) * 128 + (g & 1) * 64 + (g >> 1) * 16 + (t & 1) * 8,
                  (g & 1) ? xl : xh, (g & 1) ? yl : yh);
            __syncwarp();
            if (lane == 0) mbar_arrive(bars + (B_W + min(j, HPC)) * 8);
        }
        if (w == 3) {
            unsigned char* tp = acc_g + (c >> 2) * ACC_SET + acc_line(lane < 24 ? (c & 3) * 3 + (lane >> 3) : 16 + (c & 3)) + (lane & 7) * 16;
            mbar_wait(bars + (c < 12 ? B_FULL + 30 : B_O) * 8);
            __nanosleep(POLL_LAG_NS);
            float4 r;
#pragma unroll 1
            for (int it = 0;; it++) {
                if (lane < 24) r = ld_relaxed16(tp);
                if (__all_sync(0xffffffffu, lane >= 24 || r.z == (float)NC)) break;
                if (it > SPIN_LIMIT) __trap();
            }
            if (lane < 24) sts64(sb + OFF_T + lane * 8, __float_as_uint(r.x), __float_as_uint(r.y));
            __syncwarp();
            if (lane == 0) mbar_arrive(bars + B_T * 8);
            asm volatile("st.global.v4.u32 [%0], {%1,%1,%1,%1};" :: "l"(tp), "r"(0) : "memory");
        }
    }
}

static CUtensorMap make_map(const void* p, uint64_t cols, uint64_t rows, uint32_t box_rows,
                            CUtensorMapL2promotion promo = CU_TENSOR_MAP_L2_PROMOTION_NONE) {
    typedef CUresult (*EncodeFn)(CUtensorMap*, CUtensorMapDataType, cuuint32_t, void*, const cuuint64_t*, const cuuint64_t*,
                                 const cuuint32_t*, const cuuint32_t*, CUtensorMapInterleave, CUtensorMapSwizzle,
                                 CUtensorMapL2promotion, CUtensorMapFloatOOBfill);
    void* fn = nullptr;
    cudaDriverEntryPointQueryResult qr;
    cudaGetDriverEntryPoint("cuTensorMapEncodeTiled", &fn, cudaEnableDefault, &qr);
    CUtensorMap m;
    const cuuint64_t dims[2] = {cols, rows};
    const cuuint64_t strides[1] = {cols * 2};
    const cuuint32_t box[2] = {64, box_rows};
    const cuuint32_t estr[2] = {1, 1};
    ((EncodeFn)fn)(&m, CU_TENSOR_MAP_DATA_TYPE_BFLOAT16, 2, (void*)p, dims, strides, box, estr, CU_TENSOR_MAP_INTERLEAVE_NONE,
                   CU_TENSOR_MAP_SWIZZLE_128B, promo, CU_TENSOR_MAP_FLOAT_OOB_FILL_NONE);
    return m;
}

}

extern "C" void kernel_launch(void* const* d_in, const int* in_sizes, int n_in, void* d_out, int out_size) {
    using namespace lf;
    void* acc = nullptr;
    cudaGetSymbolAddress(&acc, g_acc);
    acc = (void*)(((uintptr_t)acc + ACC_GROUP - 1) & ~(uintptr_t)(ACC_GROUP - 1));
    cudaFuncSetAttribute(linformer_decode_kernel, cudaFuncAttributeMaxDynamicSharedMemorySize, SMEM_BYTES);
    int dev = 0, mem_khz = 0, bus_bits = 0;
    cudaGetDevice(&dev);
    cudaDeviceGetAttribute(&mem_khz, cudaDevAttrMemoryClockRate, dev);
    cudaDeviceGetAttribute(&bus_bits, cudaDevAttrGlobalMemoryBusWidth, dev);
    const double bytes_per_ns = 0.9775 * 2e-6 * mem_khz * (bus_bits / 8);
    const int period_ns = bytes_per_ns > 1.0 ? (int)(NCTA * STAGE_B / bytes_per_ns) : 0;
    cudaLaunchAttribute attr;
    attr.id = cudaLaunchAttributeCooperative;
    attr.val.cooperative = 1;
    cudaLaunchConfig_t cfg = {};
    cfg.gridDim = dim3(NCTA);
    cfg.blockDim = dim3(NWARPS * 32);
    cfg.dynamicSmemBytes = SMEM_BYTES;
    cfg.stream = cudaStreamPerThread;
    cfg.attrs = &attr;
    cfg.numAttrs = 1;
    cudaLaunchKernelEx(&cfg, linformer_decode_kernel,
                       (const __nv_bfloat16*)d_in[1], (const __nv_bfloat16*)d_in[0], (__nv_bfloat16*)d_out, (unsigned char*)acc, period_ns,
                       make_map(d_in[2], 64, (uint64_t)H * SKV * 3, 96),
                       make_map(d_in[2], DH, (uint64_t)H * SKV, 32, CU_TENSOR_MAP_L2_PROMOTION_L2_128B),
                       make_map(d_in[3], SKV, 64, 64), make_map(d_in[4], SKV, 64, 64));
}
```
